```python
import torch

def _softmax(x, axis=-1):
    return torch.softmax(x, dim=axis)
def _gelu(x):
    return torch.nn.functional.gelu(x, approximate="tanh")
def _silu(x):
    return torch.nn.functional.silu(x)
def _sigmoid(x):
    return torch.sigmoid(x)
def _layernorm(x, axis=-1, eps=1e-5):
    m = x.mean(dim=axis, keepdim=True)
    v = x.var(dim=axis, keepdim=True, unbiased=False)
    return (x - m) / torch.sqrt(v + eps)
def _scatter_add(tgt, idx, src, axis=0):
    return tgt.clone().index_add_(axis, idx, src)
def _segment_sum(src, seg, n):
    out = torch.zeros((n,) + src.shape[1:], dtype=src.dtype)
    return out.index_add_(0, seg, src)
def _pad(x, pw):
    flat = tuple(v for pair in reversed(pw) for v in pair)
    return torch.nn.functional.pad(x, flat)

kernel_name = 'standalone__gqa_block_cached__near_ridge'

def setup_inputs():

    _w = (lambda a: (lambda t: t.to(torch.bfloat16) if t.is_floating_point() else t)(torch.as_tensor(a)))
    B, Sq, D = 8, 160, 576
    Hq, Hkv, Sk, Dh = 32, 16, 2048, 128
    assert Hq % Hkv == 0, (Hq, Hkv)
    return {
        "x": _w((lambda *s: torch.randn(*s, dtype=torch.bfloat16) * 0.8)(B, Sq, D)),
        "k_cache": _w((lambda *s: torch.randn(*s, dtype=torch.bfloat16) * 0.8)(B, Hkv, Sk, Dh)),
        "v_cache": _w((lambda *s: torch.randn(*s, dtype=torch.bfloat16) * 0.05)(B, Hkv, Sk, Dh)),
        "wq": _w((lambda *s: torch.randn(*s, dtype=torch.bfloat16) * 0.8)(D, Hq * Dh) * (D ** -0.5)),
        "wo": _w((lambda *s: torch.randn(*s, dtype=torch.bfloat16) * 0.05)(Hq * Dh, D) * ((Hq * Dh) ** -0.5)),
    }

def reference(x, k_cache, v_cache, wq, wo):
    B, Sq, D = x.shape
    Hq, Dh = 32, 128
    Hkv = k_cache.shape[1]
    rep = Hq // Hkv
    q = (lambda x, *d: x.permute(*d))((x @ wq).reshape(B, Sq, Hq, Dh), 0, 2, 1, 3)
    k = (lambda x, n, axis: torch.repeat_interleave(x, n, dim=axis))(k_cache, rep, axis=1)
    v = (lambda x, n, axis: torch.repeat_interleave(x, n, dim=axis))(v_cache, rep, axis=1)
    scores = torch.einsum("bhqd,bhkd->bhqk", q, k) * (Dh ** -0.5)
    p = _softmax(scores, axis=-1)
    o = torch.einsum("bhqk,bhkd->bhqd", p, v)
    return (lambda x, *d: x.permute(*d))(o, 0, 2, 1, 3).reshape(B, Sq, Hq * Dh) @ wo
```

```cpp
#include <cuda_runtime.h>
#include <cuda_bf16.h>
#include <cuda.h>
#include <stdint.h>

namespace {

constexpr int NB = 8, SQ = 160, DM = 576, HKV = 16, SK = 2048;
constexpr int NBLK = SK / 64;
constexpr int NQC = DM / 64;
constexpr int NMT = DM / 64;

constexpr uint32_t KB = 1024;
constexpr uint32_t SM_Q = 0;
constexpr uint32_t SM_P = 80 * KB;
constexpr uint32_t QSTAGE = 52 * KB;
constexpr uint32_t SM_K0 = 208 * KB;
constexpr uint32_t SM_V0 = 192 * KB;
constexpr uint32_t SM_BAR = 224 * KB;
constexpr uint32_t SMEM_BYTES = 224 * KB + 1024 + 1024;

constexpr uint32_t BAR_FULL_Q = 0, BAR_EMPTY_Q = 9, BAR_FULL_K = 18, BAR_FULL_V = 22, BAR_EMPTY_K = 26,
                   BAR_EMPTY_V = 30, BAR_FULL_W = 34, BAR_EMPTY_W = 43, BAR_COUNT = 52;

constexpr float SCALE_LOG2 = 0.08838834764831845f * 1.4426950408889634f;
constexpr float RESCALE_TH = 8.0f;

constexpr int PART_VECS = NMT * 10 * 128;

__device__ uint4 g_part[(size_t)NB * HKV * PART_VECS];
__device__ unsigned int g_cnt[NB * 32];

__device__ __forceinline__ uint32_t smem_u32(const void* p) { return (uint32_t)__cvta_generic_to_shared(p); }

__device__ __forceinline__ void mbar_init(uint32_t bar, uint32_t cnt) {
    asm volatile("mbarrier.init.shared::cta.b64 [%0], %1;" ::"r"(bar), "r"(cnt) : "memory");
}
__device__ __forceinline__ void mbar_expect_tx(uint32_t bar, uint32_t bytes) {
    asm volatile("mbarrier.arrive.expect_tx.shared::cta.b64 _, [%0], %1;" ::"r"(bar), "r"(bytes) : "memory");
}
__device__ __forceinline__ void mbar_arrive(uint32_t bar) {
    asm volatile("mbarrier.arrive.shared::cta.b64 _, [%0];" ::"r"(bar) : "memory");
}
__device__ __forceinline__ void mbar_wait(uint32_t bar, uint32_t parity) {
    asm volatile(
        "{\n.reg .pred p;\n.reg .u32 n;\n"
        "mov.u32 n, 0;\n"
        "WAIT_LOOP:\n"
        "mbarrier.try_wait.parity.shared::cta.b64 p, [%0], %1;\n"
        "@p bra WAIT_DONE;\n"
        "add.u32 n, n, 1;\n"
        "setp.lt.u32 p, n, 131072;\n"
        "@p bra WAIT_LOOP;\n"
        "WAIT_DONE:\n}\n" ::"r"(bar), "r"(parity) : "memory");
}
__device__ __forceinline__ void bar_sync(uint32_t id, uint32_t n) {
    asm volatile("bar.sync %0, %1;" ::"r"(id), "r"(n) : "memory");
}
__device__ __forceinline__ void bar_arrive(uint32_t id, uint32_t n) {
    asm volatile("bar.arrive %0, %1;" ::"r"(id), "r"(n) : "memory");
}
__device__ __forceinline__ void fence_async_smem() { asm volatile("fence.proxy.async.shared::cta;" ::: "memory"); }

__device__ __forceinline__ void tma_2d(uint32_t dst, const CUtensorMap* tm, int c0, int c1, uint32_t bar) {
    asm volatile(
        "cp.async.bulk.tensor.2d.shared::cluster.global.mbarrier::complete_tx::bytes [%0], [%1, {%3, %4}], [%2];"
        ::"r"(dst), "l"(tm), "r"(bar), "r"(c0), "r"(c1) : "memory");
}
__device__ __forceinline__ void tma_3d(uint32_t dst, const CUtensorMap* tm, int c0, int c1, int c2, uint32_t bar) {
    asm volatile(
        "cp.async.bulk.tensor.3d.shared::cluster.global.mbarrier::complete_tx::bytes [%0], [%1, {%3, %4, %5}], [%2];"
        ::"r"(dst), "l"(tm), "r"(bar), "r"(c0), "r"(c1), "r"(c2) : "memory");
}
__device__ __forceinline__ void tma_pf_2d(const CUtensorMap* tm, int c0, int c1) {
    asm volatile("cp.async.bulk.prefetch.tensor.2d.L2.global [%0, {%1, %2}];" ::"l"(tm), "r"(c0), "r"(c1) : "memory");
}
__device__ __forceinline__ void tma_pf_3d(const CUtensorMap* tm, int c0, int c1, int c2) {
    asm volatile("cp.async.bulk.prefetch.tensor.3d.L2.global [%0, {%1, %2, %3}];" ::"l"(tm), "r"(c0), "r"(c1), "r"(c2)
                 : "memory");
}
__device__ __forceinline__ void bulk_pf(const void* p, uint32_t bytes) {
    asm volatile("cp.async.bulk.prefetch.L2.global [%0], %1;" ::"l"(p), "r"(bytes) : "memory");
}
__device__ __forceinline__ void prefetch_tmap(const CUtensorMap* tm) {
    asm volatile("prefetch.tensormap [%0];" ::"l"(tm) : "memory");
}

__device__ __forceinline__ uint64_t mkdesc(uint32_t addr, uint32_t lbo) {
    return (uint64_t)((addr & 0x3FFFF) >> 4) | ((uint64_t)(lbo >> 4) << 16) | ((uint64_t)(1024 >> 4) << 32) |
           (1ull << 62);
}
__device__ __forceinline__ void wg_fence() { asm volatile("wgmma.fence.sync.aligned;" ::: "memory"); }
__device__ __forceinline__ void wg_commit() { asm volatile("wgmma.commit_group.sync.aligned;" ::: "memory"); }
template <int N>
__device__ __forceinline__ void wg_wait() { asm volatile("wgmma.wait_group.sync.aligned %0;" ::"n"(N) : "memory"); }

#define F8(c, a, o) c(a[o + 0]), c(a[o + 1]), c(a[o + 2]), c(a[o + 3]), c(a[o + 4]), c(a[o + 5]), c(a[o + 6]), c(a[o + 7])
#define RW(x) "+f"(x)
#define WO(x) "=f"(x)
#define L32 "{%0,%1,%2,%3,%4,%5,%6,%7,%8,%9,%10,%11,%12,%13,%14,%15,%16,%17,%18,%19,%20,%21,%22,%23,%24,%25,%26,%27,%28,%29,%30,%31}"
#define L64 "{%0,%1,%2,%3,%4,%5,%6,%7,%8,%9,%10,%11,%12,%13,%14,%15,%16,%17,%18,%19,%20,%21,%22,%23,%24,%25,%26,%27,%28,%29,%30,%31," \
            "%32,%33,%34,%35,%36,%37,%38,%39,%40,%41,%42,%43,%44,%45,%46,%47,%48,%49,%50,%51,%52,%53,%54,%55,%56,%57,%58,%59,%60,%61,%62,%63}"
#define L80 "{%0,%1,%2,%3,%4,%5,%6,%7,%8,%9,%10,%11,%12,%13,%14,%15,%16,%17,%18,%19,%20,%21,%22,%23,%24,%25,%26,%27,%28,%29,%30,%31," \
            "%32,%33,%34,%35,%36,%37,%38,%39,%40,%41,%42,%43,%44,%45,%46,%47,%48,%49,%50,%51,%52,%53,%54,%55,%56,%57,%58,%59,%60,%61,%62,%63," \
            "%64,%65,%66,%67,%68,%69,%70,%71,%72,%73,%74,%75,%76,%77,%78,%79}"

__device__ __forceinline__ void mma_qk_first(float (&d)[32], uint64_t da, uint64_t db) {
    asm volatile("{\n.reg .pred p;\nsetp.ne.b32 p, 0, 0;\n"
                 "wgmma.mma_async.sync.aligned.m64n64k16.f32.bf16.bf16 " L32 ", %32, %33, p, 1, 1, 0, 0;\n}\n"
                 : F8(WO, d, 0), F8(WO, d, 8), F8(WO, d, 16), F8(WO, d, 24) : "l"(da), "l"(db));
}
__device__ __forceinline__ void mma_qk(float (&d)[32], uint64_t da, uint64_t db) {
    asm volatile("{\n.reg .pred p;\nsetp.eq.b32 p, 0, 0;\n"
                 "wgmma.mma_async.sync.aligned.m64n64k16.f32.bf16.bf16 " L32 ", %32, %33, p, 1, 1, 0, 0;\n}\n"
                 : F8(RW, d, 0), F8(RW, d, 8), F8(RW, d, 16), F8(RW, d, 24) : "l"(da), "l"(db));
}
#define L60 "{%0,%1,%2,%3,%4,%5,%6,%7,%8,%9,%10,%11,%12,%13,%14,%15,%16,%17,%18,%19,%20,%21,%22,%23,%24,%25,%26,%27,%28,%29,%30,%31," \
            "%32,%33,%34,%35,%36,%37,%38,%39,%40,%41,%42,%43,%44,%45,%46,%47,%48,%49,%50,%51,%52,%53,%54,%55,%56,%57,%58,%59}"
__device__ __forceinline__ void mma_pv120(float (&d)[64], uint32_t a0, uint32_t a1, uint32_t a2, uint32_t a3, uint64_t db) {
    asm volatile("{\n.reg .pred p;\nsetp.eq.b32 p, 0, 0;\n"
                 "wgmma.mma_async.sync.aligned.m64n120k16.f32.bf16.bf16 " L60 ", {%60,%61,%62,%63}, %64, p, 1, 1, 1;\n}\n"
                 : F8(RW, d, 0), F8(RW, d, 8), F8(RW, d, 16), F8(RW, d, 24), F8(RW, d, 32), F8(RW, d, 40), F8(RW, d, 48),
                   RW(d[56]), RW(d[57]), RW(d[58]), RW(d[59])
                 : "r"(a0), "r"(a1), "r"(a2), "r"(a3), "l"(db));
}
__device__ __forceinline__ void hmma16816(float& c0, float& c1, float& c2, float& c3, uint32_t a0, uint32_t a1, uint32_t a2,
                                          uint32_t a3, uint32_t b0, uint32_t b1) {
    asm volatile("mma.sync.aligned.m16n8k16.row.col.f32.bf16.bf16.f32 {%0,%1,%2,%3}, {%4,%5,%6,%7}, {%8,%9}, {%0,%1,%2,%3};"
                 : "+f"(c0), "+f"(c1), "+f"(c2), "+f"(c3) : "r"(a0), "r"(a1), "r"(a2), "r"(a3), "r"(b0), "r"(b1));
}
__device__ __forceinline__ void ldsm_x4_t(uint32_t addr, uint32_t& r0, uint32_t& r1, uint32_t& r2, uint32_t& r3) {
    asm volatile("ldmatrix.sync.aligned.m8n8.x4.trans.shared.b16 {%0,%1,%2,%3}, [%4];"
                 : "=r"(r0), "=r"(r1), "=r"(r2), "=r"(r3) : "r"(addr) : "memory");
}
__device__ __forceinline__ void mma_pv_ss(float (&d)[64], uint64_t da, uint64_t db) {
    asm volatile("{\n.reg .pred p;\nsetp.eq.b32 p, 0, 0;\n"
                 "wgmma.mma_async.sync.aligned.m64n128k16.f32.bf16.bf16 " L64 ", %64, %65, p, 1, 1, 0, 1;\n}\n"
                 : F8(RW, d, 0), F8(RW, d, 8), F8(RW, d, 16), F8(RW, d, 24), F8(RW, d, 32), F8(RW, d, 40), F8(RW, d, 48),
                   F8(RW, d, 56)
                 : "l"(da), "l"(db));
}
__device__ __forceinline__ void mma_proj(float (&d)[80], uint64_t da, uint64_t db) {
    asm volatile("{\n.reg .pred p;\nsetp.eq.b32 p, 0, 0;\n"
                 "wgmma.mma_async.sync.aligned.m64n160k16.f32.bf16.bf16 " L80 ", %80, %81, p, 1, 1, 1, 0;\n}\n"
                 : F8(RW, d, 0), F8(RW, d, 8), F8(RW, d, 16), F8(RW, d, 24), F8(RW, d, 32), F8(RW, d, 40), F8(RW, d, 48),
                   F8(RW, d, 56), F8(RW, d, 64), F8(RW, d, 72)
                 : "l"(da), "l"(db));
}
__device__ __forceinline__ void mma_proj_first(float (&d)[80], uint64_t da, uint64_t db) {
    asm volatile("{\n.reg .pred p;\nsetp.ne.b32 p, 0, 0;\n"
                 "wgmma.mma_async.sync.aligned.m64n160k16.f32.bf16.bf16 " L80 ", %80, %81, p, 1, 1, 1, 0;\n}\n"
                 : F8(WO, d, 0), F8(WO, d, 8), F8(WO, d, 16), F8(WO, d, 24), F8(WO, d, 32), F8(WO, d, 40), F8(WO, d, 48),
                   F8(WO, d, 56), F8(WO, d, 64), F8(WO, d, 72)
                 : "l"(da), "l"(db));
}

__device__ __forceinline__ uint32_t pack_bf16(float lo, float hi) {
    uint32_t r;
    asm("cvt.rn.bf16x2.f32 %0, %1, %2;" : "=r"(r) : "f"(hi), "f"(lo));
    return r;
}
__device__ __forceinline__ float ex2(float x) {
    float y;
    asm("ex2.approx.ftz.f32 %0, %1;" : "=f"(y) : "f"(x));
    return y;
}
__device__ __forceinline__ void stsm_x4(uint32_t addr, uint32_t r0, uint32_t r1, uint32_t r2, uint32_t r3) {
    asm volatile("stmatrix.sync.aligned.m8n8.x4.shared.b16 [%0], {%1,%2,%3,%4};" ::"r"(addr), "r"(r0), "r"(r1), "r"(r2),
                 "r"(r3) : "memory");
}
__device__ __forceinline__ void stsm_x4_t(uint32_t addr, uint32_t r0, uint32_t r1, uint32_t r2, uint32_t r3) {
    asm volatile("stmatrix.sync.aligned.m8n8.x4.trans.shared.b16 [%0], {%1,%2,%3,%4};" ::"r"(addr), "r"(r0), "r"(r1),
                 "r"(r2), "r"(r3) : "memory");
}

__device__ __forceinline__ void issue_qk(float (&s)[32], uint32_t qaddr, uint32_t kaddr) {
    const uint64_t dq = mkdesc(qaddr, 16), dk = mkdesc(kaddr, 16);
    mma_qk_first(s, dq, dk);
#pragma unroll
    for (int k = 1; k < 8; k++) {
        const uint32_t off = ((k >> 2) * 8192 + (k & 3) * 32) >> 4;
        mma_qk(s, dq + off, dk + off);
    }
}
__device__ __forceinline__ void issue_pv(float (&o)[64], const uint32_t (&p)[16], uint32_t vaddr) {
    const uint64_t dv = mkdesc(vaddr, 8192);
#pragma unroll
    for (int k = 0; k < 4; k++) mma_pv120(o, p[4 * k], p[4 * k + 1], p[4 * k + 2], p[4 * k + 3], dv + k * (2048 >> 4));
}

__device__ __forceinline__ void issue_pv_ss(float (&o)[64], uint32_t paddr, uint32_t vaddr) {
    const uint64_t dp = mkdesc(paddr, 16), dv = mkdesc(vaddr, 8192);
#pragma unroll
    for (int k = 0; k < 4; k++) mma_pv_ss(o, dp + k * 2, dv + k * (2048 >> 4));
}
__device__ __forceinline__ void store_p(const float (&s)[32], uint32_t pa) {
#pragma unroll
    for (int j = 0; j < 8; j += 2)
        stsm_x4(pa ^ (j << 4), pack_bf16(s[4 * j], s[4 * j + 1]), pack_bf16(s[4 * j + 2], s[4 * j + 3]),
                pack_bf16(s[4 * j + 4], s[4 * j + 5]), pack_bf16(s[4 * j + 6], s[4 * j + 7]));
    fence_async_smem();
}

__device__ __forceinline__ void softmax_tile(float (&s)[32], float (&o)[64], float& m0, float& m1, float& l0, float& l1) {
    float x0 = fmaxf(s[0], s[1]), x1 = fmaxf(s[2], s[3]);
#pragma unroll
    for (int j = 1; j < 8; j++) {
        x0 = fmaxf(x0, fmaxf(s[4 * j], s[4 * j + 1]));
        x1 = fmaxf(x1, fmaxf(s[4 * j + 2], s[4 * j + 3]));
    }
    x0 = fmaxf(x0, __shfl_xor_sync(0xffffffffu, x0, 1));
    x1 = fmaxf(x1, __shfl_xor_sync(0xffffffffu, x1, 1));
    x0 = fmaxf(x0, __shfl_xor_sync(0xffffffffu, x0, 2));
    x1 = fmaxf(x1, __shfl_xor_sync(0xffffffffu, x1, 2));
    x0 *= SCALE_LOG2;
    x1 *= SCALE_LOG2;
    const bool need = (x0 > m0 + RESCALE_TH) || (x1 > m1 + RESCALE_TH);
    if (__any_sync(0xffffffffu, need)) {
        const float n0 = fmaxf(m0, x0), n1 = fmaxf(m1, x1);
        const float a0 = ex2(m0 - n0), a1 = ex2(m1 - n1);
        m0 = n0;
        m1 = n1;
        l0 *= a0;
        l1 *= a1;
#pragma unroll
        for (int j = 0; j < 16; j++) {
            o[4 * j] *= a0;
            o[4 * j + 1] *= a0;
            o[4 * j + 2] *= a1;
            o[4 * j + 3] *= a1;
        }
    }
#pragma unroll
    for (int j = 0; j < 8; j++) {
        s[4 * j] = ex2(fmaf(s[4 * j], SCALE_LOG2, -m0));
        s[4 * j + 1] = ex2(fmaf(s[4 * j + 1], SCALE_LOG2, -m0));
        s[4 * j + 2] = ex2(fmaf(s[4 * j + 2], SCALE_LOG2, -m1));
        s[4 * j + 3] = ex2(fmaf(s[4 * j + 3], SCALE_LOG2, -m1));
        l0 += s[4 * j] + s[4 * j + 1];
        l1 += s[4 * j + 2] + s[4 * j + 3];
    }
}
__device__ __forceinline__ void pack_p(uint32_t (&p)[16], const float (&s)[32]) {
#pragma unroll
    for (int i = 0; i < 16; i++) p[i] = pack_bf16(s[2 * i], s[2 * i + 1]);
}

__device__ __forceinline__ void store_o_tile(const float (&o)[64], float l0, float l1, uint32_t rowaddr, uint32_t t) {
    l0 += __shfl_xor_sync(0xffffffffu, l0, 1);
    l1 += __shfl_xor_sync(0xffffffffu, l1, 1);
    l0 += __shfl_xor_sync(0xffffffffu, l0, 2);
    l1 += __shfl_xor_sync(0xffffffffu, l1, 2);
    const float r0 = 1.0f / l0, r1 = 1.0f / l1;
#pragma unroll
    for (int j = 0; j < 16; j += 2) {
        const uint32_t a = rowaddr + (j >> 3) * 20480 + (t ^ ((j & 7) << 4));
        stsm_x4(a, pack_bf16(o[4 * j] * r0, o[4 * j + 1] * r0), pack_bf16(o[4 * j + 2] * r1, o[4 * j + 3] * r1),
                pack_bf16(o[4 * j + 4] * r0, o[4 * j + 5] * r0), pack_bf16(o[4 * j + 6] * r1, o[4 * j + 7] * r1));
    }
}

__device__ __forceinline__ void acc_bf16x2(float& a, float& b, uint32_t v) {
    a += __uint_as_float(v << 16);
    b += __uint_as_float(v & 0xffff0000u);
}

template <bool IS_PRODUCER_WG>
__device__ __forceinline__ void oproj_phase(uint32_t sb, int wg, int b, int kvh, bool producer, const CUtensorMap* tmWo,
                                            __nv_bfloat16* __restrict__ out) {
    const uint32_t bars = sb + SM_BAR;
    const int tid = threadIdx.x & 127;
    uint4* mypart = g_part + (size_t)(b * HKV + kvh) * PART_VECS;
    const uint64_t dob = mkdesc(sb + SM_Q, 16);
#pragma unroll 1
    for (int it = 0; it < 3; it++) {
        const int mt = wg + 3 * it;
        float acc[80];
        mbar_wait(bars + 8 * (BAR_FULL_W + mt), 0);
        const uint64_t dw = mkdesc(sb + SM_V0 - (mt & 3) * 32 * KB, 16);
        bar_sync(1 + wg, 256);
        wg_fence();
        mma_proj_first(acc, dw, dob);
#pragma unroll
        for (int ks = 1; ks < 16; ks++)
            mma_proj(acc, dw + ks * (2048 >> 4), dob + (((ks >> 2) * 20480 + (ks & 3) * 32) >> 4));
        wg_commit();
        if (mt != NMT - 1) bar_arrive(1 + (wg == 2 ? 0 : wg + 1), 256);
        if (IS_PRODUCER_WG) {
            if (producer) {
                if (it == 0) {
                    for (int t = 4; t < 6; t++) {
                        mbar_wait(bars + 8 * (BAR_EMPTY_W + t - 4), 0);
                        mbar_expect_tx(bars + 8 * (BAR_FULL_W + t), 32 * KB);
                        tma_2d(sb + SM_V0 - (t & 3) * 32 * KB, tmWo, t * 64, kvh * 256, bars + 8 * (BAR_FULL_W + t));
                    }
                } else if (it == 1) {
                    for (int t = 7; t < 9; t++) {
                        mbar_wait(bars + 8 * (BAR_EMPTY_W + t - 4), 0);
                        mbar_expect_tx(bars + 8 * (BAR_FULL_W + t), 32 * KB);
                        tma_2d(sb + SM_V0 - (t & 3) * 32 * KB, tmWo, t * 64, kvh * 256, bars + 8 * (BAR_FULL_W + t));
                    }
                }
            }
            __syncwarp();
        }
        wg_wait<0>();
        if ((threadIdx.x & 31) == 0) mbar_arrive(bars + 8 * (BAR_EMPTY_W + mt));
        if (IS_PRODUCER_WG) {
            if (producer && it == 0) {
                mbar_wait(bars + 8 * (BAR_EMPTY_W + 2), 0);
                mbar_expect_tx(bars + 8 * (BAR_FULL_W + 6), 32 * KB);
                tma_2d(sb + SM_V0 - (6 & 3) * 32 * KB, tmWo, 6 * 64, kvh * 256, bars + 8 * (BAR_FULL_W + 6));
            }
            __syncwarp();
        }
#pragma unroll
        for (int i = 0; i < 10; i++) {
            uint4 v;
            v.x = pack_bf16(acc[8 * i], acc[8 * i + 1]);
            v.y = pack_bf16(acc[8 * i + 2], acc[8 * i + 3]);
            v.z = pack_bf16(acc[8 * i + 4], acc[8 * i + 5]);
            v.w = pack_bf16(acc[8 * i + 6], acc[8 * i + 7]);
            __stcg(mypart + (mt * 10 + i) * 128 + tid, v);
        }
    }
    __threadfence();
    bar_sync(0, 384);
    if (threadIdx.x == 0) {
        unsigned int* cnt = &g_cnt[b * 32];
        const unsigned int old = atomicAdd(cnt, 1u);
        const unsigned int target = (old / HKV + 1) * HKV;
        unsigned int n = 0, v;
        do {
            asm volatile("ld.acquire.gpu.global.u32 %0, [%1];" : "=r"(v) : "l"(cnt) : "memory");
            if (++n > (1u << 22)) break;
        } while ((int)(v - target) < 0);
        __threadfence();
    }
    bar_sync(0, 384);
    const uint4* bp = g_part + (size_t)b * HKV * PART_VECS;
#pragma unroll 1
    for (int v = threadIdx.x; v < 720; v += 384) {
        const int vec = kvh * 720 + v;
        uint4 r[HKV];
#pragma unroll
        for (int h = 0; h < HKV; h++) r[h] = __ldcg(bp + (size_t)h * PART_VECS + vec);
        float a[8];
#pragma unroll
        for (int i = 0; i < 8; i++) a[i] = 0.f;
#pragma unroll
        for (int h = 0; h < HKV; h++) {
            acc_bf16x2(a[0], a[1], r[h].x);
            acc_bf16x2(a[2], a[3], r[h].y);
            acc_bf16x2(a[4], a[5], r[h].z);
            acc_bf16x2(a[6], a[7], r[h].w);
        }
        const int t = vec & 127, mi = vec >> 7, mt = mi / 10, i = mi - mt * 10;
        const int col = mt * 64 + (t >> 5) * 16 + ((t & 31) >> 2);
        const int tok = i * 16 + (t & 3) * 2;
        __nv_bfloat16* o = out + ((size_t)b * SQ + tok) * DM + col;
        o[0] = __float2bfloat16(a[0]);
        o[DM] = __float2bfloat16(a[1]);
        o[8] = __float2bfloat16(a[2]);
        o[DM + 8] = __float2bfloat16(a[3]);
        o[8 * DM] = __float2bfloat16(a[4]);
        o[9 * DM] = __float2bfloat16(a[5]);
        o[8 * DM + 8] = __float2bfloat16(a[6]);
        o[9 * DM + 8] = __float2bfloat16(a[7]);
    }
}

__global__ void __launch_bounds__(384, 1)
gqa_fused_kernel(const __grid_constant__ CUtensorMap tmX, const __grid_constant__ CUtensorMap tmWq,
                 const __grid_constant__ CUtensorMap tmK, const __grid_constant__ CUtensorMap tmV,
                 const __grid_constant__ CUtensorMap tmWo, const __nv_bfloat16* __restrict__ gk,
                 const __nv_bfloat16* __restrict__ gv, __nv_bfloat16* __restrict__ out) {
    extern __shared__ __align__(1024) uint8_t smem_raw[];
    const uint32_t sb = (smem_u32(smem_raw) + 1023u) & ~1023u;
    const uint32_t bars = sb + SM_BAR;
    const int wg = __shfl_sync(0xffffffffu, (int)(threadIdx.x >> 7), 0);
    const int warp = __shfl_sync(0xffffffffu, (int)((threadIdx.x >> 5) & 3), 0);
    const int lane = threadIdx.x & 31;
    const int b = blockIdx.x >> 4, kvh = blockIdx.x & 15;

    if (threadIdx.x == 0) {
        for (int i = 0; i < (int)BAR_COUNT; i++) {
            uint32_t cnt = 1;
            if (i >= (int)BAR_EMPTY_Q && i < (int)BAR_FULL_K) cnt = 8;
            if (i >= (int)BAR_EMPTY_K && i < (int)BAR_FULL_W) cnt = 12;
            if (i >= (int)BAR_EMPTY_W) cnt = 4;
            mbar_init(bars + 8 * i, cnt);
        }
        asm volatile("fence.mbarrier_init.release.cluster;" ::: "memory");
    }
    __syncthreads();

    if (wg < 2) {
        asm volatile("setmaxnreg.inc.sync.aligned.u32 192;");
        {
            float q0[80], q1[80];
#pragma unroll
            for (int i = 0; i < 80; i++) { q0[i] = 0.f; q1[i] = 0.f; }
#pragma unroll 1
            for (int c = 0; c < NQC; c++) {
                const uint32_t st = sb + ((8 - c) & 3) * QSTAGE;
                mbar_wait(bars + 8 * (BAR_FULL_Q + c), 0);
                const uint64_t dx = mkdesc(st, 16);
                const uint64_t dw = mkdesc(st + 20 * KB + wg * 16 * KB, 16);
                wg_fence();
#pragma unroll
                for (int ks = 0; ks < 4; ks++) {
                    mma_proj(q0, dw + ks * (2048 >> 4), dx + ks * 2);
                    mma_proj(q1, dw + ((8192 + ks * 2048) >> 4), dx + ks * 2);
                }
                wg_commit();
                wg_wait<1>();
                if (c > 0 && lane == 0) mbar_arrive(bars + 8 * (BAR_EMPTY_Q + c - 1));
            }
            wg_wait<0>();
            bar_sync(4, 256);
            const uint32_t chunk = 2 * warp + ((lane >> 3) & 1);
            const uint32_t la = sb + SM_Q + (lane >> 4) * 1024 + (lane & 7) * 128 + ((chunk ^ (lane & 7)) << 4);
#pragma unroll
            for (int jj = 0; jj < 10; jj++) {
                uint32_t off;
                if (jj < 4) off = wg * 16384 + jj * 2048;
                else if (jj < 8) off = (2 + wg) * 16384 + (jj - 4) * 2048;
                else off = 4 * 16384 + wg * 4096 + (jj - 8) * 2048;
                const int j = 2 * jj;
                stsm_x4_t(la + off, pack_bf16(q0[4 * j], q0[4 * j + 1]), pack_bf16(q0[4 * j + 2], q0[4 * j + 3]),
                          pack_bf16(q0[4 * j + 4], q0[4 * j + 5]), pack_bf16(q0[4 * j + 6], q0[4 * j + 7]));
                stsm_x4_t(la + off + 8192, pack_bf16(q1[4 * j], q1[4 * j + 1]), pack_bf16(q1[4 * j + 2], q1[4 * j + 3]),
                          pack_bf16(q1[4 * j + 4], q1[4 * j + 5]), pack_bf16(q1[4 * j + 6], q1[4 * j + 7]));
            }
            fence_async_smem();
            bar_sync(0, 384);
        }
        float oa[64], ob[64], s[32];
#pragma unroll
        for (int i = 0; i < 64; i++) { oa[i] = 0.f; ob[i] = 0.f; }
        float ma0 = -INFINITY, ma1 = -INFINITY, mb0 = -INFINITY, mb1 = -INFINITY;
        float la0 = 0.f, la1 = 0.f, lb0 = 0.f, lb1 = 0.f;
        const uint32_t qa = sb + SM_Q + wg * 32768, qb = qa + 16384;
        const uint32_t my_turn = 1 + wg, next_turn = 2 + wg;
        const uint32_t pbuf = sb + SM_P + wg * 8192;
        const uint32_t pa = pbuf + (warp * 16 + ((lane >> 3) & 1) * 8 + (lane & 7)) * 128 + (((lane >> 4) ^ (lane & 7)) << 4);

        mbar_wait(bars + 8 * BAR_FULL_K, 0);
        bar_sync(my_turn, 256);
        wg_fence();
        issue_qk(s, qa, sb + SM_K0);
        wg_commit();
        bar_arrive(next_turn, 256);
        wg_wait<0>();
        softmax_tile(s, oa, ma0, ma1, la0, la1);
        store_p(s, pa);
#pragma unroll 1
        for (int j = 0; j < NBLK; j++) {
            const uint32_t st = j & 3, ph = (j >> 2) & 1;
            const uint32_t kaddr = sb + SM_K0 - st * 32 * KB, vaddr = sb + SM_V0 - st * 32 * KB;
            mbar_wait(bars + 8 * (BAR_FULL_V + st), ph);
            bar_sync(my_turn, 256);
            wg_fence();
            issue_qk(s, qb, kaddr);
            wg_commit();
            issue_pv_ss(oa, pbuf, vaddr);
            wg_commit();
            bar_arrive(next_turn, 256);
            wg_wait<1>();
            if (lane == 0) mbar_arrive(bars + 8 * (BAR_EMPTY_K + st));
            softmax_tile(s, ob, mb0, mb1, lb0, lb1);
            wg_wait<0>();
            store_p(s, pa);
            if (j + 1 < NBLK) {
                const uint32_t st1 = (j + 1) & 3, ph1 = ((j + 1) >> 2) & 1;
                mbar_wait(bars + 8 * (BAR_FULL_K + st1), ph1);
                bar_sync(my_turn, 256);
                wg_fence();
                issue_qk(s, qa, sb + SM_K0 - st1 * 32 * KB);
                wg_commit();
                issue_pv_ss(ob, pbuf, vaddr);
                wg_commit();
                bar_arrive(next_turn, 256);
                wg_wait<1>();
                softmax_tile(s, oa, ma0, ma1, la0, la1);
                wg_wait<0>();
                if (lane == 0) mbar_arrive(bars + 8 * (BAR_EMPTY_V + st));
                store_p(s, pa);
            } else {
                bar_sync(5 + wg, 128);
                wg_fence();
                issue_pv_ss(ob, pbuf, vaddr);
                wg_commit();
                wg_wait<0>();
                if (lane == 0) mbar_arrive(bars + 8 * (BAR_EMPTY_V + st));
            }
        }
        bar_sync(0, 384);
        {
            const uint32_t row = wg * 64 + warp * 16 + ((lane >> 3) & 1) * 8 + (lane & 7);
            const uint32_t t = ((lane >> 4) ^ (lane & 7)) << 4;
            store_o_tile(oa, la0, la1, sb + SM_Q + row * 128, t);
            store_o_tile(ob, lb0, lb1, sb + SM_Q + 2 * 20480 + row * 128, t);
        }
        fence_async_smem();
        bar_sync(0, 384);
        oproj_phase<false>(sb, wg, b, kvh, false, &tmWo, out);
    } else {
        asm volatile("setmaxnreg.dec.sync.aligned.u32 120;");
        const bool producer = (threadIdx.x == 256);
        const int kvrow = (b * HKV + kvh) * SK;
        const __nv_bfloat16* kp = gk + (size_t)kvrow * 128;
        const __nv_bfloat16* vp = gv + (size_t)kvrow * 128;
        constexpr int PF = 5;
        if (producer) {
            prefetch_tmap(&tmX);
            prefetch_tmap(&tmWq);
            prefetch_tmap(&tmK);
            prefetch_tmap(&tmV);
            for (int c = 0; c < 4; c++) {
                const uint32_t st = sb + ((8 - c) & 3) * QSTAGE;
                mbar_expect_tx(bars + 8 * (BAR_FULL_Q + c), QSTAGE);
                tma_2d(st, &tmX, c * 64, b * SQ, bars + 8 * (BAR_FULL_Q + c));
                tma_3d(st + 20 * KB, &tmWq, 0, c * 64, kvh * 4, bars + 8 * (BAR_FULL_Q + c));
            }
            for (int c = 4; c < NQC; c++) {
                tma_pf_2d(&tmX, c * 64, b * SQ);
                tma_pf_3d(&tmWq, 0, c * 64, kvh * 4);
            }
            mbar_expect_tx(bars + 8 * BAR_FULL_K, 16 * KB);
            tma_3d(sb + SM_K0, &tmK, 0, kvrow, 0, bars + 8 * BAR_FULL_K);
            bulk_pf(vp, 16 * KB);
            for (int j = 1; j < 4; j++) {
                bulk_pf(kp + j * 64 * 128, 16 * KB);
                bulk_pf(vp + j * 64 * 128, 16 * KB);
            }
            for (int c = 4; c < NQC; c++) {
                const uint32_t st = sb + ((8 - c) & 3) * QSTAGE;
                mbar_wait(bars + 8 * (BAR_EMPTY_Q + c - 4), 0);
                mbar_expect_tx(bars + 8 * (BAR_FULL_Q + c), QSTAGE);
                tma_2d(st, &tmX, c * 64, b * SQ, bars + 8 * (BAR_FULL_Q + c));
                tma_3d(st + 20 * KB, &tmWq, 0, c * 64, kvh * 4, bars + 8 * (BAR_FULL_Q + c));
                bulk_pf(kp + c * 64 * 128, 16 * KB);
                bulk_pf(vp + c * 64 * 128, 16 * KB);
            }
            for (int i = 1; i < 8; i++) {
                if (i == 1) mbar_wait(bars + 8 * (BAR_EMPTY_Q + 5), 0);
                if (i == 4) mbar_wait(bars + 8 * (BAR_EMPTY_Q + 6), 0);
                if (i == 7) mbar_wait(bars + 8 * (BAR_EMPTY_Q + 7), 0);
                const int j = i >> 1;
                const uint32_t bar = bars + 8 * (((i & 1) ? BAR_FULL_V : BAR_FULL_K) + j);
                mbar_expect_tx(bar, 16 * KB);
                tma_3d(sb + SM_K0 - i * 16 * KB, (i & 1) ? &tmV : &tmK, 0, kvrow + j * 64, 0, bar);
            }
            prefetch_tmap(&tmWo);
        }
        __syncwarp();
        bar_sync(0, 384);

        float o[64], s[32];
        uint32_t p[16];
#pragma unroll
        for (int i = 0; i < 64; i++) o[i] = 0.f;
        float m0 = -INFINITY, m1 = -INFINITY, l0 = 0.f, l1 = 0.f;
        const uint32_t qc = sb + SM_Q + 4 * 16384;
        const uint32_t vtail = 8192 + lane * 128 + ((7 ^ (lane & 7)) << 4);
        bar_arrive(1, 256);
#pragma unroll 1
        for (int j = 0; j < NBLK; j++) {
            const uint32_t st = j & 3, ph = (j >> 2) & 1;
            const uint32_t stp = (j + 3) & 3, php = ((j - 1) >> 2) & 1;
            mbar_wait(bars + 8 * (BAR_FULL_K + st), ph);
            wg_wait<0>();
            bar_sync(3, 256);
            wg_fence();
            issue_qk(s, qc, sb + SM_K0 - st * 32 * KB);
            wg_commit();
            bar_arrive(1, 256);
            wg_wait<0>();
            if (lane == 0) {
                mbar_arrive(bars + 8 * (BAR_EMPTY_K + st));
                if (j > 0) mbar_arrive(bars + 8 * (BAR_EMPTY_V + stp));
            }
            softmax_tile(s, o, m0, m1, l0, l1);
            pack_p(p, s);
            if (producer && j > 0) {
                mbar_wait(bars + 8 * (BAR_EMPTY_V + stp), php);
                if (j + 3 < NBLK) {
                    mbar_expect_tx(bars + 8 * (BAR_FULL_V + stp), 16 * KB);
                    tma_3d(sb + SM_V0 - stp * 32 * KB, &tmV, 0, kvrow + (j + 3) * 64, 0, bars + 8 * (BAR_FULL_V + stp));
                    if (j + 3 + PF < NBLK) bulk_pf(vp + (j + 3 + PF) * 64 * 128, 16 * KB);
                } else {
                    const int t = j + 3 - NBLK;
                    mbar_expect_tx(bars + 8 * (BAR_FULL_W + t), 32 * KB);
                    tma_2d(sb + SM_V0 - stp * 32 * KB, &tmWo, t * 64, kvh * 256, bars + 8 * (BAR_FULL_W + t));
                }
            }
            __syncwarp();
            mbar_wait(bars + 8 * (BAR_FULL_V + st), ph);
            {
                const uint32_t va = sb + SM_V0 - st * 32 * KB + vtail;
                uint32_t b0, b1, b2, b3;
                ldsm_x4_t(va, b0, b1, b2, b3);
                hmma16816(o[60], o[61], o[62], o[63], p[0], p[1], p[2], p[3], b0, b1);
                hmma16816(o[60], o[61], o[62], o[63], p[4], p[5], p[6], p[7], b2, b3);
                ldsm_x4_t(va + 4096, b0, b1, b2, b3);
                hmma16816(o[60], o[61], o[62], o[63], p[8], p[9], p[10], p[11], b0, b1);
                hmma16816(o[60], o[61], o[62], o[63], p[12], p[13], p[14], p[15], b2, b3);
            }
            bar_sync(3, 256);
            wg_fence();
            issue_pv(o, p, sb + SM_V0 - st * 32 * KB);
            wg_commit();
            if (j + 1 < NBLK) bar_arrive(1, 256);
            if (producer) {
                mbar_wait(bars + 8 * (BAR_EMPTY_K + st), ph);
                if (j + 4 < NBLK) {
                    mbar_expect_tx(bars + 8 * (BAR_FULL_K + st), 16 * KB);
                    tma_3d(sb + SM_K0 - st * 32 * KB, &tmK, 0, kvrow + (j + 4) * 64, 0, bars + 8 * (BAR_FULL_K + st));
                    if (j + 4 + PF < NBLK) bulk_pf(kp + (j + 4 + PF) * 64 * 128, 16 * KB);
                }
                if (j >= 12 && j < 12 + NMT) tma_pf_2d(&tmWo, (j - 12) * 64, kvh * 256);
            }
            __syncwarp();
        }
        wg_wait<0>();
        if (lane == 0) mbar_arrive(bars + 8 * (BAR_EMPTY_V + 3));
        bar_sync(0, 384);
        if (producer) {
            mbar_expect_tx(bars + 8 * (BAR_FULL_W + 3), 32 * KB);
            tma_2d(sb + SM_V0 - 3 * 32 * KB, &tmWo, 3 * 64, kvh * 256, bars + 8 * (BAR_FULL_W + 3));
        }
        __syncwarp();
        {
            const uint32_t row = 128 + (warp & 1) * 16 + ((lane >> 3) & 1) * 8 + (lane & 7);
            const uint32_t t = ((lane >> 4) ^ (lane & 7)) << 4;
            store_o_tile(o, l0, l1, sb + SM_Q + (warp >> 1) * 2 * 20480 + row * 128, t);
        }
        fence_async_smem();
        bar_sync(0, 384);
        bar_arrive(1, 256);
        oproj_phase<true>(sb, wg, b, kvh, producer, &tmWo, out);
    }
}

typedef CUresult (*EncodeTiledFn)(CUtensorMap*, CUtensorMapDataType, cuuint32_t, void*, const cuuint64_t*,
                                  const cuuint64_t*, const cuuint32_t*, const cuuint32_t*, CUtensorMapInterleave,
                                  CUtensorMapSwizzle, CUtensorMapL2promotion, CUtensorMapFloatOOBfill);

void encode(EncodeTiledFn fn, CUtensorMap* tm, const void* ptr, int rank, const cuuint64_t* dims,
            const cuuint64_t* strides, const cuuint32_t* box) {
    cuuint32_t es[3] = {1, 1, 1};
    fn(tm, CU_TENSOR_MAP_DATA_TYPE_BFLOAT16, rank, const_cast<void*>(ptr), dims, strides, box, es,
       CU_TENSOR_MAP_INTERLEAVE_NONE, CU_TENSOR_MAP_SWIZZLE_128B, CU_TENSOR_MAP_L2_PROMOTION_L2_256B,
       CU_TENSOR_MAP_FLOAT_OOB_FILL_NONE);
}

}

extern "C" void kernel_launch(void* const* d_in, const int* in_sizes, int n_in, void* d_out, int out_size) {
    const __nv_bfloat16* x = (const __nv_bfloat16*)d_in[0];
    const __nv_bfloat16* kc = (const __nv_bfloat16*)d_in[1];
    const __nv_bfloat16* vc = (const __nv_bfloat16*)d_in[2];
    const __nv_bfloat16* wq = (const __nv_bfloat16*)d_in[3];
    const __nv_bfloat16* wo = (const __nv_bfloat16*)d_in[4];

    void* fnp = nullptr;
    cudaDriverEntryPointQueryResult qres;
    cudaGetDriverEntryPoint("cuTensorMapEncodeTiled", &fnp, cudaEnableDefault, &qres);
    EncodeTiledFn fn = (EncodeTiledFn)fnp;

    CUtensorMap tmX, tmWq, tmK, tmV, tmWo;
    {
        cuuint64_t d[2] = {DM, (cuuint64_t)NB * SQ}, s[1] = {DM * 2};
        cuuint32_t bx[2] = {64, SQ};
        encode(fn, &tmX, x, 2, d, s, bx);
    }
    {
        cuuint64_t d[3] = {64, DM, 64}, s[2] = {4096 * 2, 128};
        cuuint32_t bx[3] = {64, 64, 4};
        encode(fn, &tmWq, wq, 3, d, s, bx);
    }
    {
        cuuint64_t d[3] = {64, (cuuint64_t)NB * HKV * SK, 2}, s[2] = {256, 128};
        cuuint32_t bx[3] = {64, 64, 2};
        encode(fn, &tmK, kc, 3, d, s, bx);
        encode(fn, &tmV, vc, 3, d, s, bx);
    }
    {
        cuuint64_t d[2] = {DM, 4096}, s[1] = {DM * 2};
        cuuint32_t bx[2] = {64, 256};
        encode(fn, &tmWo, wo, 2, d, s, bx);
    }
    cudaFuncSetAttribute(gqa_fused_kernel, cudaFuncAttributeMaxDynamicSharedMemorySize, SMEM_BYTES);
    gqa_fused_kernel<<<NB * HKV, 384, SMEM_BYTES>>>(tmX, tmWq, tmK, tmV, tmWo, kc, vc, (__nv_bfloat16*)d_out);
}
```

```cpp
#include <cuda_runtime.h>
#include <cuda_bf16.h>
#include <cuda.h>
#include <stdint.h>

#define FV 3
#define PFD 0

namespace {

constexpr int NB = 8, SQ = 160, DM = 576, HKV = 16, SK = 2048;
constexpr int NBLK = SK / 64;
constexpr int NQC = DM / 64;
constexpr int NMT = DM / 64;

constexpr uint32_t KB = 1024;
constexpr uint32_t sb = 1024;
constexpr uint32_t SM_Q = 0;
constexpr uint32_t SM_P = 80 * KB;
constexpr uint32_t QSTAGE = 52 * KB;
constexpr uint32_t SM_RING0 = 208 * KB;
constexpr uint32_t NSLOT = 7;
constexpr uint32_t SM_BAR = 224 * KB;
constexpr uint32_t SMEM_BYTES = 224 * KB + 1024;

constexpr uint32_t BAR_FULL_Q = 0, BAR_EMPTY_Q = 9, BAR_FULL = 18, BAR_EMPTY = 25, BAR_FULL_W = 32, BAR_RX = 50,
                   BAR_FREE = 59, BAR_COUNT = 65;

constexpr float SCALE_LOG2 = 0.08838834764831845f * 1.4426950408889634f;
constexpr float RESCALE_SUM = 1.0995116e12f;
constexpr float ZERO_REF_RANGE = 24.0f;

constexpr int NPAIR = HKV / 2;
constexpr int PART_VECS = NMT * 10 * 128;

__device__ uint4 g_part[(size_t)NB * NPAIR * PART_VECS];
__device__ unsigned int g_hint[NB * 32];
__device__ unsigned int g_epoch[NB * HKV];

#define STAMP(i)

__device__ __forceinline__ uint32_t smem_u32(const void* p) { return (uint32_t)__cvta_generic_to_shared(p); }

__device__ __forceinline__ void mbar_init(uint32_t bar, uint32_t cnt) {
    asm volatile("mbarrier.init.shared::cta.b64 [%0], %1;" ::"r"(bar), "r"(cnt) : "memory");
}
__device__ __forceinline__ void mbar_expect_tx(uint32_t bar, uint32_t bytes) {
    asm volatile("mbarrier.arrive.expect_tx.shared::cta.b64 _, [%0], %1;" ::"r"(bar), "r"(bytes) : "memory");
}
__device__ __forceinline__ void mbar_arrive(uint32_t bar) {
    asm volatile("mbarrier.arrive.shared::cta.b64 _, [%0];" ::"r"(bar) : "memory");
}
__device__ __forceinline__ void mbar_wait(uint32_t bar, uint32_t parity) {
    asm volatile(
        "{\n.reg .pred p;\n.reg .u32 n;\n"
        "mov.u32 n, 0;\n"
        "WAIT_LOOP:\n"
        "mbarrier.try_wait.parity.shared::cta.b64 p, [%0], %1;\n"
        "@p bra WAIT_DONE;\n"
        "add.u32 n, n, 1;\n"
        "setp.lt.u32 p, n, 131072;\n"
        "@p bra WAIT_LOOP;\n"
        "WAIT_DONE:\n}\n" ::"r"(bar), "r"(parity) : "memory");
}
__device__ __forceinline__ void mbar_wait_cluster(uint32_t bar, uint32_t parity) {
    asm volatile(
        "{\n.reg .pred p;\n.reg .u32 n;\n"
        "mov.u32 n, 0;\n"
        "WAIT_LOOP:\n"
        "mbarrier.try_wait.parity.acquire.cluster.shared::cta.b64 p, [%0], %1;\n"
        "@p bra WAIT_DONE;\n"
        "add.u32 n, n, 1;\n"
        "setp.lt.u32 p, n, 131072;\n"
        "@p bra WAIT_LOOP;\n"
        "WAIT_DONE:\n}\n" ::"r"(bar), "r"(parity) : "memory");
}
__device__ __forceinline__ void mbar_arrive_remote(uint32_t bar) {
    asm volatile("mbarrier.arrive.relaxed.cluster.shared::cluster.b64 _, [%0];" ::"r"(bar) : "memory");
}
__device__ __forceinline__ uint32_t mapa(uint32_t addr, uint32_t rank) {
    uint32_t r;
    asm("mapa.shared::cluster.u32 %0, %1, %2;" : "=r"(r) : "r"(addr), "r"(rank));
    return r;
}
__device__ __forceinline__ void st_async_v4(uint32_t addr, uint32_t x, uint32_t y, uint32_t z, uint32_t w, uint32_t bar) {
    asm volatile("st.async.weak.shared::cluster.mbarrier::complete_tx::bytes.v4.b32 [%0], {%1,%2,%3,%4}, [%5];" ::"r"(addr),
                 "r"(x), "r"(y), "r"(z), "r"(w), "r"(bar) : "memory");
}
__device__ __forceinline__ uint4 lds_v4(uint32_t addr) {
    uint4 v;
    asm volatile("ld.shared.v4.b32 {%0,%1,%2,%3}, [%4];" : "=r"(v.x), "=r"(v.y), "=r"(v.z), "=r"(v.w) : "r"(addr) : "memory");
    return v;
}
__device__ __forceinline__ void bar_sync(uint32_t id, uint32_t n) {
    asm volatile("bar.sync %0, %1;" ::"r"(id), "r"(n) : "memory");
}
__device__ __forceinline__ void bar_arrive(uint32_t id, uint32_t n) {
    asm volatile("bar.arrive %0, %1;" ::"r"(id), "r"(n) : "memory");
}
__device__ __forceinline__ void turn_wait(int wg) {
    if (wg == 0) asm volatile("bar.sync 1, 256;" ::: "memory");
    else asm volatile("bar.sync 2, 256;" ::: "memory");
}
__device__ __forceinline__ void turn_pass(int wg) {
    if (wg == 0) asm volatile("bar.arrive 2, 256;" ::: "memory");
    else asm volatile("bar.arrive 3, 256;" ::: "memory");
}
__device__ __forceinline__ bool elect_one() {
    uint32_t p;
    asm volatile("{\n.reg .pred P;\nelect.sync _|P, 0xffffffff;\nselp.u32 %0, 1, 0, P;\n}\n" : "=r"(p));
    return p != 0;
}
__device__ __forceinline__ void fence_async_smem() { asm volatile("fence.proxy.async.shared::cta;" ::: "memory"); }

__device__ __forceinline__ void tma_2d(uint32_t dst, const CUtensorMap* tm, int c0, int c1, uint32_t bar) {
    asm volatile(
        "cp.async.bulk.tensor.2d.shared::cluster.global.mbarrier::complete_tx::bytes [%0], [%1, {%3, %4}], [%2];"
        ::"r"(dst), "l"(tm), "r"(bar), "r"(c0), "r"(c1) : "memory");
}
__device__ __forceinline__ void tma_3d(uint32_t dst, const CUtensorMap* tm, int c0, int c1, int c2, uint32_t bar) {
    asm volatile(
        "cp.async.bulk.tensor.3d.shared::cluster.global.mbarrier::complete_tx::bytes [%0], [%1, {%3, %4, %5}], [%2];"
        ::"r"(dst), "l"(tm), "r"(bar), "r"(c0), "r"(c1), "r"(c2) : "memory");
}
__device__ __forceinline__ void tma_pf_2d(const CUtensorMap* tm, int c0, int c1) {
    asm volatile("cp.async.bulk.prefetch.tensor.2d.L2.global [%0, {%1, %2}];" ::"l"(tm), "r"(c0), "r"(c1) : "memory");
}
__device__ __forceinline__ void tma_pf_3d(const CUtensorMap* tm, int c0, int c1, int c2) {
    asm volatile("cp.async.bulk.prefetch.tensor.3d.L2.global [%0, {%1, %2, %3}];" ::"l"(tm), "r"(c0), "r"(c1), "r"(c2)
                 : "memory");
}
__device__ __forceinline__ void bulk_pf(const void* p, uint32_t bytes) {
    asm volatile("cp.async.bulk.prefetch.L2.global [%0], %1;" ::"l"(p), "r"(bytes) : "memory");
}
__device__ __forceinline__ void prefetch_tmap(const CUtensorMap* tm) {
    asm volatile("prefetch.tensormap [%0];" ::"l"(tm) : "memory");
}

__device__ __forceinline__ uint32_t desc_lo(uint32_t addr, uint32_t lbo) { return (addr >> 4) | ((lbo >> 4) << 16); }
__device__ __forceinline__ uint64_t mkdesc(uint32_t lo) {
    uint64_t d;
    asm("mov.b64 %0, {%1, %2};" : "=l"(d) : "r"(lo), "r"(0x40000040u));
    return d;
}
__device__ __forceinline__ void wg_fence() { asm volatile("wgmma.fence.sync.aligned;" ::: "memory"); }
__device__ __forceinline__ void wg_commit() { asm volatile("wgmma.commit_group.sync.aligned;" ::: "memory"); }
template <int N>
__device__ __forceinline__ void wg_wait() { asm volatile("wgmma.wait_group.sync.aligned %0;" ::"n"(N) : "memory"); }

#define F8(c, a, o) c(a[o + 0]), c(a[o + 1]), c(a[o + 2]), c(a[o + 3]), c(a[o + 4]), c(a[o + 5]), c(a[o + 6]), c(a[o + 7])
#define RW(x) "+f"(x)
#define WO(x) "=f"(x)
#define L32 "{%0,%1,%2,%3,%4,%5,%6,%7,%8,%9,%10,%11,%12,%13,%14,%15,%16,%17,%18,%19,%20,%21,%22,%23,%24,%25,%26,%27,%28,%29,%30,%31}"
#define L64 "{%0,%1,%2,%3,%4,%5,%6,%7,%8,%9,%10,%11,%12,%13,%14,%15,%16,%17,%18,%19,%20,%21,%22,%23,%24,%25,%26,%27,%28,%29,%30,%31," \
            "%32,%33,%34,%35,%36,%37,%38,%39,%40,%41,%42,%43,%44,%45,%46,%47,%48,%49,%50,%51,%52,%53,%54,%55,%56,%57,%58,%59,%60,%61,%62,%63}"
#define L80 "{%0,%1,%2,%3,%4,%5,%6,%7,%8,%9,%10,%11,%12,%13,%14,%15,%16,%17,%18,%19,%20,%21,%22,%23,%24,%25,%26,%27,%28,%29,%30,%31," \
            "%32,%33,%34,%35,%36,%37,%38,%39,%40,%41,%42,%43,%44,%45,%46,%47,%48,%49,%50,%51,%52,%53,%54,%55,%56,%57,%58,%59,%60,%61,%62,%63," \
            "%64,%65,%66,%67,%68,%69,%70,%71,%72,%73,%74,%75,%76,%77,%78,%79}"

__device__ __forceinline__ void mma_qk_first(float (&d)[32], uint64_t da, uint64_t db) {
    asm volatile("{\n.reg .pred p;\nsetp.ne.b32 p, 0, 0;\n"
                 "wgmma.mma_async.sync.aligned.m64n64k16.f32.bf16.bf16 " L32 ", %32, %33, p, 1, 1, 0, 0;\n}\n"
                 : F8(WO, d, 0), F8(WO, d, 8), F8(WO, d, 16), F8(WO, d, 24) : "l"(da), "l"(db));
}
__device__ __forceinline__ void mma_qk(float (&d)[32], uint64_t da, uint64_t db) {
    asm volatile("{\n.reg .pred p;\nsetp.eq.b32 p, 0, 0;\n"
                 "wgmma.mma_async.sync.aligned.m64n64k16.f32.bf16.bf16 " L32 ", %32, %33, p, 1, 1, 0, 0;\n}\n"
                 : F8(RW, d, 0), F8(RW, d, 8), F8(RW, d, 16), F8(RW, d, 24) : "l"(da), "l"(db));
}
__device__ __forceinline__ void mma_pv(float (&d)[64], uint32_t a0, uint32_t a1, uint32_t a2, uint32_t a3, uint64_t db) {
    asm volatile("{\n.reg .pred p;\nsetp.eq.b32 p, 0, 0;\n"
                 "wgmma.mma_async.sync.aligned.m64n128k16.f32.bf16.bf16 " L64 ", {%64,%65,%66,%67}, %68, p, 1, 1, 1;\n}\n"
                 : F8(RW, d, 0), F8(RW, d, 8), F8(RW, d, 16), F8(RW, d, 24), F8(RW, d, 32), F8(RW, d, 40), F8(RW, d, 48),
                   F8(RW, d, 56)
                 : "r"(a0), "r"(a1), "r"(a2), "r"(a3), "l"(db));
}
__device__ __forceinline__ float split_copy(float x) {
    float y;
    asm volatile("add.rn.f32 %0, %1, 0f80000000;" : "=f"(y) : "f"(x));
    return y;
}
__device__ __forceinline__ void hmma16816(float& c0, float& c1, float& c2, float& c3, uint32_t a0, uint32_t a1, uint32_t a2,
                                          uint32_t a3, uint32_t b0, uint32_t b1) {
    asm volatile("mma.sync.aligned.m16n8k16.row.col.f32.bf16.bf16.f32 {%0,%1,%2,%3}, {%4,%5,%6,%7}, {%8,%9}, {%0,%1,%2,%3};"
                 : "+f"(c0), "+f"(c1), "+f"(c2), "+f"(c3) : "r"(a0), "r"(a1), "r"(a2), "r"(a3), "r"(b0), "r"(b1));
}
__device__ __forceinline__ void ldsm_x4(uint32_t addr, uint32_t& r0, uint32_t& r1, uint32_t& r2, uint32_t& r3) {
    asm volatile("ldmatrix.sync.aligned.m8n8.x4.shared.b16 {%0,%1,%2,%3}, [%4];"
                 : "=r"(r0), "=r"(r1), "=r"(r2), "=r"(r3) : "r"(addr) : "memory");
}
__device__ __forceinline__ void ldsm_x4_t(uint32_t addr, uint32_t& r0, uint32_t& r1, uint32_t& r2, uint32_t& r3) {
    asm volatile("ldmatrix.sync.aligned.m8n8.x4.trans.shared.b16 {%0,%1,%2,%3}, [%4];"
                 : "=r"(r0), "=r"(r1), "=r"(r2), "=r"(r3) : "r"(addr) : "memory");
}
__device__ __forceinline__ void mma_pv_ss(float (&d)[64], uint64_t da, uint64_t db) {
    asm volatile("{\n.reg .pred p;\nsetp.eq.b32 p, 0, 0;\n"
                 "wgmma.mma_async.sync.aligned.m64n128k16.f32.bf16.bf16 " L64 ", %64, %65, p, 1, 1, 0, 1;\n}\n"
                 : F8(RW, d, 0), F8(RW, d, 8), F8(RW, d, 16), F8(RW, d, 24), F8(RW, d, 32), F8(RW, d, 40), F8(RW, d, 48),
                   F8(RW, d, 56)
                 : "l"(da), "l"(db));
}
__device__ __forceinline__ void mma_proj(float (&d)[80], uint64_t da, uint64_t db) {
    asm volatile("{\n.reg .pred p;\nsetp.eq.b32 p, 0, 0;\n"
                 "wgmma.mma_async.sync.aligned.m64n160k16.f32.bf16.bf16 " L80 ", %80, %81, p, 1, 1, 1, 0;\n}\n"
                 : F8(RW, d, 0), F8(RW, d, 8), F8(RW, d, 16), F8(RW, d, 24), F8(RW, d, 32), F8(RW, d, 40), F8(RW, d, 48),
                   F8(RW, d, 56), F8(RW, d, 64), F8(RW, d, 72)
                 : "l"(da), "l"(db));
}
__device__ __forceinline__ void mma_proj_first(float (&d)[80], uint64_t da, uint64_t db) {
    asm volatile("{\n.reg .pred p;\nsetp.ne.b32 p, 0, 0;\n"
                 "wgmma.mma_async.sync.aligned.m64n160k16.f32.bf16.bf16 " L80 ", %80, %81, p, 1, 1, 1, 0;\n}\n"
                 : F8(WO, d, 0), F8(WO, d, 8), F8(WO, d, 16), F8(WO, d, 24), F8(WO, d, 32), F8(WO, d, 40), F8(WO, d, 48),
                   F8(WO, d, 56), F8(WO, d, 64), F8(WO, d, 72)
                 : "l"(da), "l"(db));
}

__device__ __forceinline__ uint32_t pack_bf16(float lo, float hi) {
    uint32_t r;
    asm("cvt.rn.bf16x2.f32 %0, %1, %2;" : "=r"(r) : "f"(hi), "f"(lo));
    return r;
}
__device__ __forceinline__ float ex2(float x) {
    float y;
    asm("ex2.approx.ftz.f32 %0, %1;" : "=f"(y) : "f"(x));
    return y;
}
__device__ __forceinline__ void stsm_x4(uint32_t addr, uint32_t r0, uint32_t r1, uint32_t r2, uint32_t r3) {
    asm volatile("stmatrix.sync.aligned.m8n8.x4.shared.b16 [%0], {%1,%2,%3,%4};" ::"r"(addr), "r"(r0), "r"(r1), "r"(r2),
                 "r"(r3) : "memory");
}
__device__ __forceinline__ void stsm_x4_t(uint32_t addr, uint32_t r0, uint32_t r1, uint32_t r2, uint32_t r3) {
    asm volatile("stmatrix.sync.aligned.m8n8.x4.trans.shared.b16 [%0], {%1,%2,%3,%4};" ::"r"(addr), "r"(r0), "r"(r1),
                 "r"(r2), "r"(r3) : "memory");
}

__device__ __forceinline__ void issue_qk(float (&s)[32], uint32_t qaddr, uint32_t kaddr) {
    const uint32_t dq = desc_lo(qaddr, 16), dk = desc_lo(kaddr, 16);
    mma_qk_first(s, mkdesc(dq), mkdesc(dk));
#pragma unroll
    for (int k = 1; k < 8; k++) {
        const uint32_t off = ((k >> 2) * 8192 + (k & 3) * 32) >> 4;
        mma_qk(s, mkdesc(dq + off), mkdesc(dk + off));
    }
}
__device__ __forceinline__ void issue_pv(float (&o)[64], const uint32_t (&p)[16], uint32_t vaddr) {
    const uint32_t dv = desc_lo(vaddr, 8192);
#pragma unroll
    for (int k = 0; k < 4; k++) mma_pv(o, p[4 * k], p[4 * k + 1], p[4 * k + 2], p[4 * k + 3], mkdesc(dv + k * (2048 >> 4)));
}
__device__ __forceinline__ void issue_pv_ss(float (&o)[64], uint32_t paddr, uint32_t vaddr) {
    const uint32_t dp = desc_lo(paddr, 128), dv = desc_lo(vaddr, 8192);
#pragma unroll
    for (int k = 0; k < 4; k++) {
        uint64_t da;
        asm("mov.b64 %0, {%1, %2};" : "=l"(da) : "r"(dp + k * (2048 >> 4)), "r"(256u >> 4));
        mma_pv_ss(o, da, mkdesc(dv + k * (2048 >> 4)));
    }
}
struct RingPos {
    uint32_t slot, par;
    __device__ __forceinline__ void next() {
        if (++slot == NSLOT) { slot = 0; par ^= 1; }
    }
};

__device__ __forceinline__ void local_max(const float (&s)[32], float& x0, float& x1) {
    float y0 = fmaxf(s[4], s[5]), y1 = fmaxf(s[6], s[7]);
    x0 = fmaxf(s[0], s[1]);
    x1 = fmaxf(s[2], s[3]);
#pragma unroll
    for (int j = 2; j < 8; j += 2) {
        x0 = fmaxf(x0, fmaxf(s[4 * j], s[4 * j + 1]));
        x1 = fmaxf(x1, fmaxf(s[4 * j + 2], s[4 * j + 3]));
        y0 = fmaxf(y0, fmaxf(s[4 * j + 4], s[4 * j + 5]));
        y1 = fmaxf(y1, fmaxf(s[4 * j + 6], s[4 * j + 7]));
    }
    x0 = fmaxf(x0, y0);
    x1 = fmaxf(x1, y1);
}
__device__ __forceinline__ void refresh_max(float x0, float x1, float (&o)[64], float& m0, float& m1, float& l0, float& l1,
                                            bool& zref) {
    x0 = fmaxf(x0, __shfl_xor_sync(0xffffffffu, x0, 1));
    x1 = fmaxf(x1, __shfl_xor_sync(0xffffffffu, x1, 1));
    x0 = fmaxf(x0, __shfl_xor_sync(0xffffffffu, x0, 2));
    x1 = fmaxf(x1, __shfl_xor_sync(0xffffffffu, x1, 2));
    float n0 = fmaxf(m0, x0), n1 = fmaxf(m1, x1);
    zref = __all_sync(0xffffffffu, fmaxf(fabsf(n0), fabsf(n1)) <= ZERO_REF_RANGE);
    if (zref) {
        n0 = 0.f;
        n1 = 0.f;
    }
    const float a0 = ex2(m0 - n0), a1 = ex2(m1 - n1);
    m0 = n0;
    m1 = n1;
    l0 *= a0;
    l1 *= a1;
#pragma unroll
    for (int j = 0; j < 16; j++) {
        o[4 * j] *= a0;
        o[4 * j + 1] *= a0;
        o[4 * j + 2] *= a1;
        o[4 * j + 3] *= a1;
    }
}

__device__ __forceinline__ void recompute_scores(float (&s)[32], uint32_t qaddr, uint32_t kaddr) {
    uint32_t tid;
    asm volatile("mov.u32 %0, %%tid.x;" : "=r"(tid));
    uint32_t rank;
    asm volatile("mov.u32 %0, %%cluster_ctarank;" : "=r"(rank));
    qaddr = mapa(qaddr, rank);
    kaddr = mapa(kaddr, rank);
    const uint32_t lane = tid & 31, warp = (tid >> 5) & 3, r7 = lane & 7;
    const uint32_t qa = qaddr + (warp * 16 + r7 + ((lane >> 3) & 1) * 8) * 128, qc = lane >> 4;
    const uint32_t ka = kaddr + (r7 + (lane >> 4) * 8) * 128, kc = (lane >> 3) & 1;
#pragma unroll
    for (int i = 0; i < 32; i++) s[i] = 0.f;
#pragma unroll 1
    for (uint32_t ks = 0; ks < 8; ks++) {
        const uint32_t h = (ks >> 2) * 8192, c = (ks & 3) * 2;
        uint32_t a0, a1, a2, a3;
        ldsm_x4(qa + h + (((c + qc) ^ r7) << 4), a0, a1, a2, a3);
#pragma unroll
        for (int np = 0; np < 4; np++) {
            uint32_t b0, b1, b2, b3;
            ldsm_x4(ka + h + np * 2048 + (((c + kc) ^ r7) << 4), b0, b1, b2, b3);
            hmma16816(s[8 * np], s[8 * np + 1], s[8 * np + 2], s[8 * np + 3], a0, a1, a2, a3, b0, b1);
            hmma16816(s[8 * np + 4], s[8 * np + 5], s[8 * np + 6], s[8 * np + 7], a0, a1, a2, a3, b2, b3);
        }
    }
}

template <bool SUB, bool TO_SMEM>
__device__ __forceinline__ void exp_tile(const float (&s)[32], uint32_t (&p)[16], float m0, float m1, float& t0, float& t1,
                                         uint32_t pa) {
#pragma unroll
    for (int j = 0; j < 8; j += 2) {
        const float p0 = ex2(SUB ? s[4 * j] - m0 : s[4 * j]), p1 = ex2(SUB ? s[4 * j + 1] - m0 : s[4 * j + 1]);
        const float p2 = ex2(SUB ? s[4 * j + 2] - m1 : s[4 * j + 2]), p3 = ex2(SUB ? s[4 * j + 3] - m1 : s[4 * j + 3]);
        const float p4 = ex2(SUB ? s[4 * j + 4] - m0 : s[4 * j + 4]), p5 = ex2(SUB ? s[4 * j + 5] - m0 : s[4 * j + 5]);
        const float p6 = ex2(SUB ? s[4 * j + 6] - m1 : s[4 * j + 6]), p7 = ex2(SUB ? s[4 * j + 7] - m1 : s[4 * j + 7]);
        const float u0 = (p0 + p1) + (p4 + p5), u1 = (p2 + p3) + (p6 + p7);
        t0 = j == 0 ? u0 : t0 + u0;
        t1 = j == 0 ? u1 : t1 + u1;
        p[2 * j] = pack_bf16(p0, p1);
        p[2 * j + 1] = pack_bf16(p2, p3);
        p[2 * j + 2] = pack_bf16(p4, p5);
        p[2 * j + 3] = pack_bf16(p6, p7);
        if (TO_SMEM) stsm_x4(pa + j * 1024, p[2 * j], p[2 * j + 1], p[2 * j + 2], p[2 * j + 3]);
    }
}
template <bool WAIT, bool TO_SMEM>
__device__ __forceinline__ void softmax_tile(float (&s)[32], uint32_t (&p)[16], float (&o)[64], float& m0, float& m1,
                                             float& l0, float& l1, bool& zref, bool first, uint32_t qaddr, uint32_t kaddr,
                                             uint32_t pa) {
    float t0, t1, x0, x1;
    if (__builtin_expect(!zref, 0)) goto general;
    exp_tile<false, TO_SMEM>(s, p, m0, m1, t0, t1, pa);
    if (__builtin_expect(!__any_sync(0xffffffffu, !(fmaxf(t0, t1) <= RESCALE_SUM)), 1)) goto done;
    goto recompute;
general:
    if (first) goto refresh;
    exp_tile<true, TO_SMEM>(s, p, m0, m1, t0, t1, pa);
    if (!__any_sync(0xffffffffu, !(fmaxf(t0, t1) <= RESCALE_SUM))) goto done;
recompute:
    recompute_scores(s, qaddr, kaddr);
refresh:
    if (WAIT) wg_wait<0>();
    local_max(s, x0, x1);
    refresh_max(x0, x1, o, m0, m1, l0, l1, zref);
    exp_tile<true, TO_SMEM>(s, p, m0, m1, t0, t1, pa);
done:
    if (WAIT) wg_wait<0>();
    l0 += t0;
    l1 += t1;
}
__device__ __forceinline__ void finish_l(float& l0, float& l1) {
    l0 += __shfl_xor_sync(0xffffffffu, l0, 1);
    l1 += __shfl_xor_sync(0xffffffffu, l1, 1);
    l0 += __shfl_xor_sync(0xffffffffu, l0, 2);
    l1 += __shfl_xor_sync(0xffffffffu, l1, 2);
    l0 = __fdividef(1.0f, l0);
    l1 = __fdividef(1.0f, l1);
}
__device__ __forceinline__ void pack_o_tile(uint32_t (&pk)[32], const float (&o)[64], float r0, float r1) {
#pragma unroll
    for (int j = 0; j < 16; j++) {
        pk[2 * j] = pack_bf16(o[4 * j] * r0, o[4 * j + 1] * r0);
        pk[2 * j + 1] = pack_bf16(o[4 * j + 2] * r1, o[4 * j + 3] * r1);
    }
}
__device__ __forceinline__ void store_o_tile(const uint32_t (&pk)[32], uint32_t rowaddr, uint32_t t) {
#pragma unroll
    for (int j = 0; j < 16; j += 2)
        stsm_x4(rowaddr + (j >> 3) * 20480 + (t ^ ((j & 7) << 4)), pk[2 * j], pk[2 * j + 1], pk[2 * j + 2], pk[2 * j + 3]);
}

__device__ __forceinline__ void acc_bf16x2(float& a, float& b, uint32_t v) {
    a += __uint_as_float(v << 16);
    b += __uint_as_float(v & 0xffff0000u);
}

__device__ __forceinline__ uint32_t wo_off(uint32_t w) { return SM_RING0 - ((w + 1) % NSLOT) * 16 * KB; }
__device__ __forceinline__ void load_wo_half(uint32_t sa, const CUtensorMap* tmWo, uint32_t w, int kvh) {
    const uint32_t bar = sa + SM_BAR + 8 * (BAR_FULL_W + w);
    mbar_expect_tx(bar, 16 * KB);
    tma_2d(sa + wo_off(w), tmWo, (w >> 1) * 64, kvh * 256 + (w & 1) * 128, bar);
}

__device__ __forceinline__ void st_b128(uint4* p, uint4 v) {
    asm volatile("{\n.reg .b128 t;\n.reg .b64 a, b;\nmov.b64 a, {%1, %2};\nmov.b64 b, {%3, %4};\nmov.b128 t, {a, b};\n"
                 "st.relaxed.gpu.global.b128 [%0], t;\n}\n" ::"l"(p), "r"(v.x), "r"(v.y), "r"(v.z), "r"(v.w) : "memory");
}
__device__ __forceinline__ uint4 ld_b128(const uint4* p) {
    uint4 v;
    asm volatile("{\n.reg .b128 t;\n.reg .b64 a, b;\nld.relaxed.gpu.global.b128 t, [%4];\nmov.b128 {a, b}, t;\n"
                 "mov.b64 {%0, %1}, a;\nmov.b64 {%2, %3}, b;\n}\n" : "=r"(v.x), "=r"(v.y), "=r"(v.z), "=r"(v.w) : "l"(p) : "memory");
    return v;
}

__device__ __forceinline__ void reduce_load(uint4 (&r)[NPAIR], const uint4* bp) {
#pragma unroll
    for (int h = 0; h < NPAIR; h++) r[h] = ld_b128(bp + (size_t)h * PART_VECS);
}
__device__ __forceinline__ void reduce_finish(uint4 (&r)[NPAIR], const uint4* bp, uint32_t tag, __nv_bfloat16* __restrict__ o) {
#pragma unroll 1
    for (int n = 0; n < (1 << 20); n++) {
        uint32_t late = 0;
#pragma unroll
        for (int h = 0; h < NPAIR; h++) late |= r[h].x ^ tag;
        if ((late & 1u) == 0) break;
#pragma unroll
        for (int h = 0; h < NPAIR; h++)
            if ((r[h].x ^ tag) & 1u) r[h] = ld_b128(bp + (size_t)h * PART_VECS);
    }
    float a[8];
#pragma unroll
    for (int i = 0; i < 8; i++) a[i] = 0.f;
#pragma unroll
    for (int h = 0; h < NPAIR; h++) {
        acc_bf16x2(a[0], a[1], r[h].x & ~1u);
        acc_bf16x2(a[2], a[3], r[h].y);
        acc_bf16x2(a[4], a[5], r[h].z);
        acc_bf16x2(a[6], a[7], r[h].w);
    }
    o[0] = __float2bfloat16(a[0]);
    o[DM] = __float2bfloat16(a[1]);
    o[8] = __float2bfloat16(a[2]);
    o[DM + 8] = __float2bfloat16(a[3]);
    o[8 * DM] = __float2bfloat16(a[4]);
    o[9 * DM] = __float2bfloat16(a[5]);
    o[8 * DM + 8] = __float2bfloat16(a[6]);
    o[9 * DM + 8] = __float2bfloat16(a[7]);
}

__device__ __forceinline__ void oproj_phase(uint32_t sa, int wg, int warp, int b, int kvh, const CUtensorMap* tmWo,
                                            __nv_bfloat16* __restrict__ out) {
    const uint32_t bars = sa + SM_BAR;
    const int tid = threadIdx.x & 127;
    const uint32_t rank = kvh & 1;
    const uint32_t epoch = __ldcg(&g_epoch[b * HKV + kvh]) + 1u, tag = epoch & 1u;
    uint4* mypart = g_part + (size_t)(b * NPAIR + (kvh >> 1)) * PART_VECS + wg * 1280 + rank * 640 + tid;
    const int vec = kvh * 80 + tid;
    const uint4* bp = g_part + (size_t)b * NPAIR * PART_VECS + wg * 1280 + vec;
    __nv_bfloat16* op = out + ((size_t)b * SQ + (vec >> 7) * 16 + (vec & 3) * 2) * DM + wg * 64 + ((vec & 127) >> 5) * 16 +
                        ((vec & 31) >> 2);
    const uint32_t rx = sa + SM_P + wg * 10240 + tid * 16;
    const uint32_t rx_peer = mapa(rx, rank ^ 1), bars_peer = mapa(bars, rank ^ 1);
    const uint32_t dob = desc_lo(sb + SM_Q, 16);
    if (wg == 0) {
        mbar_wait(bars + 8 * BAR_FULL_W, 0);
        mbar_wait(bars + 8 * (BAR_FULL_W + 1), 0);
    }
    bar_sync(0, 384);
    asm volatile("barrier.cluster.arrive.relaxed.aligned;" ::: "memory");
    if (wg == 2 && warp == 0 && elect_one()) load_wo_half(sa, tmWo, 6, kvh);
    __syncwarp();
    STAMP(9);
#pragma unroll 1
    for (int it = 0; it < 3; it++) {
        const int mt = wg + 3 * it;
        float acc[80];
        if (mt > 0) {
            mbar_wait(bars + 8 * (BAR_FULL_W + 2 * mt), 0);
            mbar_wait(bars + 8 * (BAR_FULL_W + 2 * mt + 1), 0);
        }
        const uint32_t dw0 = desc_lo(sb + wo_off(2 * mt), 16), dw1 = desc_lo(sb + wo_off(2 * mt + 1), 16);
        if (mt > 0) bar_sync(1 + wg, 256);
        wg_fence();
        mma_proj_first(acc, mkdesc(dw0), mkdesc(dob));
#pragma unroll
        for (int ks = 1; ks < 16; ks++)
            mma_proj(acc, mkdesc((ks < 8 ? dw0 : dw1) + (ks & 7) * (2048 >> 4)),
                     mkdesc(dob + (((ks >> 2) * 20480 + (ks & 3) * 32) >> 4)));
        wg_commit();
        if (mt != NMT - 1) bar_arrive(1 + (wg == 2 ? 0 : wg + 1), 256);
        if (it == 0) asm volatile("barrier.cluster.wait.acquire.aligned;" ::: "memory");
        else mbar_wait_cluster(bars + 8 * (BAR_FREE + mt - 3), 0);
        wg_wait<0>();
#pragma unroll
        for (int i = 0; i < 5; i++)
            st_async_v4(rx_peer + i * 2048, pack_bf16(acc[40 + 8 * i], acc[41 + 8 * i]), pack_bf16(acc[42 + 8 * i], acc[43 + 8 * i]),
                        pack_bf16(acc[44 + 8 * i], acc[45 + 8 * i]), pack_bf16(acc[46 + 8 * i], acc[47 + 8 * i]),
                        bars_peer + 8 * (BAR_RX + mt));
        if (mt <= 5) {
            bar_sync(5 + wg, 128);
            if (warp == 3 && elect_one()) {
                load_wo_half(sa, tmWo, 2 * mt + 7, kvh);
                if (mt <= 4) load_wo_half(sa, tmWo, 2 * mt + 8, kvh);
            }
            __syncwarp();
        }
        mbar_wait_cluster(bars + 8 * (BAR_RX + mt), 0);
#pragma unroll
        for (int i = 0; i < 5; i++) {
            const uint4 q = lds_v4(rx + i * 2048);
            acc_bf16x2(acc[8 * i], acc[8 * i + 1], q.x);
            acc_bf16x2(acc[8 * i + 2], acc[8 * i + 3], q.y);
            acc_bf16x2(acc[8 * i + 4], acc[8 * i + 5], q.z);
            acc_bf16x2(acc[8 * i + 6], acc[8 * i + 7], q.w);
            uint4 v;
            v.x = (pack_bf16(0.f, acc[8 * i + 1]) | (((__float_as_uint(acc[8 * i]) + 0x10000u) >> 17) << 1)) | tag;
            v.y = pack_bf16(acc[8 * i + 2], acc[8 * i + 3]);
            v.z = pack_bf16(acc[8 * i + 4], acc[8 * i + 5]);
            v.w = pack_bf16(acc[8 * i + 6], acc[8 * i + 7]);
            st_b128(mypart + it * 3840 + i * 128, v);
        }
        __syncwarp();
        if (elect_one()) {
            asm volatile("red.relaxed.gpu.global.add.u32 [%0], 1;" ::"l"(&g_hint[b * 32 + mt]) : "memory");
            if (it < 2) mbar_arrive_remote(bars_peer + 8 * (BAR_FREE + mt));
        }
        __syncwarp();
    }
    STAMP(10);
    if (tid < 80) {
        uint4 r2[NPAIR];
        reduce_load(r2, bp + 3840);
#pragma unroll 1
        for (int k = 0; k < 3; k++) {
            uint4 r[NPAIR];
            if (k == 2) {
                const unsigned int target = epoch * (HKV * 4);
                unsigned int v;
#pragma unroll 1
                for (int n = 0; n < (1 << 20); n++) {
                    asm volatile("ld.relaxed.gpu.global.u32 %0, [%1];" : "=r"(v) : "l"(&g_hint[b * 32 + wg + 6]) : "memory");
                    if ((int)(v - target) >= 0) break;
                }
                STAMP(11);
            }
            if (k == 1) {
#pragma unroll
                for (int h = 0; h < NPAIR; h++) r[h] = r2[h];
            } else {
                reduce_load(r, bp + k * 3840);
            }
            reduce_finish(r, bp + k * 3840, tag, op + k * 192);
        }
    }
    STAMP(13);
    bar_sync(4, 384);
    if (threadIdx.x == 0) g_epoch[b * HKV + kvh] = epoch;
}

__global__ void __cluster_dims__(2, 1, 1) __launch_bounds__(384, 1)
gqa_fused_kernel(const __grid_constant__ CUtensorMap tmX, const __grid_constant__ CUtensorMap tmWq,
                 const __grid_constant__ CUtensorMap tmK, const __grid_constant__ CUtensorMap tmV,
                 const __grid_constant__ CUtensorMap tmWo, const __nv_bfloat16* __restrict__ gk,
                 const __nv_bfloat16* __restrict__ gv, const __nv_bfloat16* __restrict__ gwo,
                 __nv_bfloat16* __restrict__ out) {
    extern __shared__ __align__(1024) uint8_t smem_raw[];
    const uint32_t sa = smem_u32(smem_raw);
    if ((sa & 0x3FFFFu) != sb) __trap();
    const uint32_t bars = sa + SM_BAR;
    const int wg = __shfl_sync(0xffffffffu, (int)(threadIdx.x >> 7), 0);
    const int warp = __shfl_sync(0xffffffffu, (int)((threadIdx.x >> 5) & 3), 0);
    const int lane = threadIdx.x & 31;
    const int b = blockIdx.x >> 4, kvh = blockIdx.x & 15;

    STAMP(0);
    const int kvrow = (b * HKV + kvh) * SK;
    if (wg == 2 && warp == 0) {
        if (elect_one()) {
            mbar_init(bars + 8 * BAR_FULL_Q, 1);
            asm volatile("fence.mbarrier_init.release.cluster;" ::: "memory");
            mbar_expect_tx(bars + 8 * BAR_FULL_Q, QSTAGE);
            tma_3d(sa + 20 * KB, &tmWq, 0, 0, kvh * 4, bars + 8 * BAR_FULL_Q);
            tma_2d(sa, &tmX, 0, b * SQ, bars + 8 * BAR_FULL_Q);
        }
        __syncwarp();
    } else if (wg < 2) {
        if (elect_one()) {
#pragma unroll
            for (uint32_t k = 0; k < 8; k++) {
                const uint32_t i = (wg * 4 + warp) * 8 + k + 1;
                uint32_t cnt = 1;
                if (i >= BAR_EMPTY_Q && i < BAR_FULL) cnt = 8;
                if (i >= BAR_EMPTY && i < BAR_FULL_W) cnt = 12;
                if (i >= BAR_FREE) cnt = 4;
                mbar_init(bars + 8 * i, cnt);
            }
            asm volatile("fence.mbarrier_init.release.cluster;" ::: "memory");
        }
        __syncwarp();
    }
    __syncthreads();

    if (wg < 2) {
        asm volatile("setmaxnreg.inc.sync.aligned.u32 192;");
        {
            float q0[80], q1[80];
#pragma unroll
            for (int i = 0; i < 80; i++) { q0[i] = 0.f; q1[i] = 0.f; }
#pragma unroll 1
            for (int c = 0; c < NQC; c++) {
                const uint32_t st = sb + ((8 - c) & 3) * QSTAGE;
                mbar_wait(bars + 8 * (BAR_FULL_Q + c), 0);
                if (c == 0) STAMP(1);
                if (c == 4) STAMP(2);
                const uint32_t dx = desc_lo(st, 16);
                const uint32_t dw = desc_lo(st + 20 * KB + wg * 16 * KB, 16);
                wg_fence();
#pragma unroll
                for (int ks = 0; ks < 4; ks++) {
                    mma_proj(q0, mkdesc(dw + ks * (2048 >> 4)), mkdesc(dx + ks * 2));
                    mma_proj(q1, mkdesc(dw + ((8192 + ks * 2048) >> 4)), mkdesc(dx + ks * 2));
                }
                wg_commit();
                wg_wait<1>();
                if (c > 0 && lane == 0) mbar_arrive(bars + 8 * (BAR_EMPTY_Q + c - 1));
            }
            wg_wait<0>();
            STAMP(3);
            bar_sync(4, 256);
#pragma unroll
            for (int i = 0; i < 80; i++) {
                q0[i] *= SCALE_LOG2;
                q1[i] *= SCALE_LOG2;
            }
            const uint32_t chunk = 2 * warp + ((lane >> 3) & 1);
            const uint32_t la = sa + SM_Q + (lane >> 4) * 1024 + (lane & 7) * 128 + ((chunk ^ (lane & 7)) << 4);
#pragma unroll
            for (int jj = 0; jj < 10; jj++) {
                uint32_t off;
                if (jj < 4) off = wg * 16384 + jj * 2048;
                else if (jj < 8) off = (2 + wg) * 16384 + (jj - 4) * 2048;
                else off = 4 * 16384 + wg * 4096 + (jj - 8) * 2048;
                const int j = 2 * jj;
                stsm_x4_t(la + off, pack_bf16(q0[4 * j], q0[4 * j + 1]), pack_bf16(q0[4 * j + 2], q0[4 * j + 3]),
                          pack_bf16(q0[4 * j + 4], q0[4 * j + 5]), pack_bf16(q0[4 * j + 6], q0[4 * j + 7]));
                stsm_x4_t(la + off + 8192, pack_bf16(q1[4 * j], q1[4 * j + 1]), pack_bf16(q1[4 * j + 2], q1[4 * j + 3]),
                          pack_bf16(q1[4 * j + 4], q1[4 * j + 5]), pack_bf16(q1[4 * j + 6], q1[4 * j + 7]));
            }
            fence_async_smem();
            bar_sync(0, 384);
        }
        float oa[64], ob[64], s[32];
        uint32_t p[16];
#pragma unroll
        for (int i = 0; i < 64; i++) { oa[i] = 0.f; ob[i] = 0.f; }
        float ma0 = -INFINITY, ma1 = -INFINITY, mb0 = -INFINITY, mb1 = -INFINITY;
        float la0 = 0.f, la1 = 0.f, lb0 = 0.f, lb1 = 0.f;
        bool za = false, zb = false;
        const uint32_t qa = sb + SM_Q + wg * 32768, qb = qa + 16384;
        const uint32_t pbufa = sb + SM_P + wg * 16384, pbufb = pbufa + 8192;
        uint32_t pa = sa + SM_P + wg * 16384 + (warp * 2 + ((lane >> 3) & 1)) * 256 + (lane >> 4) * 128 + (lane & 7) * 16;
        asm volatile("" : "+r"(pa));

        STAMP(4);
        turn_wait(wg);
        wg_fence();
        issue_qk(s, qa, sb + SM_RING0);
        wg_commit();
        turn_pass(wg);
        wg_wait<0>();
        softmax_tile<false, true>(s, p, oa, ma0, ma1, la0, la1, za, true, qa, sb + SM_RING0, pa);
        if (FV & 1) fence_async_smem();
        turn_wait(wg);
        uint32_t kslot = 0;
#pragma unroll 1
        for (int j = 0; j < NBLK; j++) {
            const uint32_t vslot = kslot == NSLOT - 1 ? 0 : kslot + 1;
            const uint32_t kslot1 = vslot == NSLOT - 1 ? 0 : vslot + 1;
            const uint32_t kaddr = sb + SM_RING0 - kslot * 16 * KB, vaddr = sb + SM_RING0 - vslot * 16 * KB;
            wg_fence();
            issue_qk(s, qb, kaddr);
            wg_commit();
            if (!(FV & 1)) fence_async_smem();
            issue_pv_ss(oa, pbufa, vaddr);
            wg_commit();
            turn_pass(wg);
            wg_wait<1>();
            softmax_tile<false, true>(s, p, ob, mb0, mb1, lb0, lb1, zb, j == 0, qb, kaddr, pa + 8192);
            if (elect_one()) mbar_arrive(bars + 8 * (BAR_EMPTY + kslot));
            __syncwarp();
            if (j + 1 < NBLK) {
                if (FV & 2) fence_async_smem();
                turn_wait(wg);
                wg_fence();
                issue_qk(s, qa, sb + SM_RING0 - kslot1 * 16 * KB);
                wg_commit();
                if (!(FV & 2)) fence_async_smem();
                issue_pv_ss(ob, pbufb, vaddr);
                wg_commit();
                turn_pass(wg);
                wg_wait<1>();
                softmax_tile<false, true>(s, p, oa, ma0, ma1, la0, la1, za, false, qa, sb + SM_RING0 - kslot1 * 16 * KB, pa);
                if (FV & 1) fence_async_smem();
                turn_wait(wg);
                wg_wait<0>();
                if (elect_one()) mbar_arrive(bars + 8 * (BAR_EMPTY + vslot));
                __syncwarp();
            } else {
                wg_wait<0>();
            }
            kslot = kslot1;
        }
        fence_async_smem();
        wg_fence();
        issue_pv_ss(ob, pbufb, sb + SM_RING0 - ((2 * NBLK - 1) % NSLOT) * 16 * KB);
        wg_commit();
        uint32_t pka[32];
        finish_l(la0, la1);
        finish_l(lb0, lb1);
        pack_o_tile(pka, oa, la0, la1);
        uint32_t orow = wg * 64 + warp * 16 + (kvh & 1) * 80;
        if (orow >= SQ) orow -= SQ;
        orow = sa + SM_Q + (orow + ((lane >> 3) & 1) * 8 + (lane & 7)) * 128;
        const uint32_t osw = ((lane >> 4) ^ (lane & 7)) << 4;
        bar_sync(9, 384);
        store_o_tile(pka, orow, osw);
        wg_wait<0>();
        STAMP(8);
        pack_o_tile(pka, ob, lb0, lb1);
        store_o_tile(pka, orow + 2 * 20480, osw);
        fence_async_smem();
        asm volatile("setmaxnreg.dec.sync.aligned.u32 120;");
    } else {
        asm volatile("setmaxnreg.dec.sync.aligned.u32 120;");
        const bool pwarp = (warp == 0);
        if (pwarp && elect_one()) {
#pragma unroll 1
            for (int c = 1; c < NQC; c++) {
                const uint32_t st = sa + ((8 - c) & 3) * QSTAGE;
                if (c == 4) {
                    mbar_expect_tx(bars + 8 * BAR_FULL, 16 * KB);
                    tma_3d(sa + SM_RING0, &tmK, 0, kvrow, 0, bars + 8 * BAR_FULL);
                    prefetch_tmap(&tmV);
                    for (int i = 0; i < NMT; i++) mbar_expect_tx(bars + 8 * (BAR_RX + i), 10240);
                }
                if (c >= 4) mbar_wait(bars + 8 * (BAR_EMPTY_Q + c - 4), 0);
                mbar_expect_tx(bars + 8 * (BAR_FULL_Q + c), QSTAGE);
                tma_2d(st, &tmX, c * 64, b * SQ, bars + 8 * (BAR_FULL_Q + c));
                tma_3d(st + 20 * KB, &tmWq, 0, c * 64, kvh * 4, bars + 8 * (BAR_FULL_Q + c));
            }
#pragma unroll 1
            for (int i = 1; i < 6; i++) {
                if (i == 1) mbar_wait(bars + 8 * (BAR_EMPTY_Q + 5), 0);
                if (i == 4) mbar_wait(bars + 8 * (BAR_EMPTY_Q + 6), 0);
                const uint32_t bar = bars + 8 * (BAR_FULL + i);
                mbar_expect_tx(bar, 16 * KB);
                tma_3d(sa + SM_RING0 - i * 16 * KB, (i & 1) ? &tmV : &tmK, 0, kvrow + (i >> 1) * 64, 0, bar);
            }
            if (PFD > 0) {
                bulk_pf(gk + (size_t)(kvrow + 3 * 64) * 128, PFD * 16 * KB);
                bulk_pf(gv + (size_t)(kvrow + 3 * 64) * 128, PFD * 16 * KB);
            }
            prefetch_tmap(&tmWo);
        }
        __syncwarp();
        bar_sync(0, 384);

        float o[64], s[32];
        uint32_t p[16];
#pragma unroll
        for (int i = 0; i < 64; i++) o[i] = 0.f;
        float m0 = -INFINITY, m1 = -INFINITY, l0 = 0.f, l1 = 0.f;
        bool zc = false;
        const uint32_t qc = sb + SM_Q + 4 * 16384;
        RingPos rk = {0, 0}, rvp = {NSLOT - 1, 1};
        mbar_wait(bars + 8 * BAR_FULL, 0);
        bar_arrive(1, 256);
#pragma unroll 1
        for (int j = 0; j < NBLK; j++) {
            RingPos rv = rk;
            rv.next();
            const uint32_t vaddr = sb + SM_RING0 - rv.slot * 16 * KB;
            RingPos rk1 = rv;
            rk1.next();
            mbar_wait(bars + 8 * (BAR_FULL + rv.slot), rv.par);
            bar_sync(3, 256);
            wg_fence();
            issue_qk(s, qc, sb + SM_RING0 - rk.slot * 16 * KB);
            wg_commit();
            bar_arrive(1, 256);
            if (j + 1 < NBLK) mbar_wait(bars + 8 * (BAR_FULL + rk1.slot), rk1.par);
            wg_wait<0>();
            softmax_tile<false, false>(s, p, o, m0, m1, l0, l1, zc, j == 0, qc, sb + SM_RING0 - rk.slot * 16 * KB, 0);
#pragma unroll
            for (int i = 60; i < 64; i++) o[i] = split_copy(o[i]);
            bar_sync(3, 256);
            wg_fence();
            issue_pv(o, p, vaddr);
            wg_commit();
            if (j + 1 < NBLK) bar_arrive(1, 256);
            if (elect_one()) mbar_arrive(bars + 8 * (BAR_EMPTY + rk.slot));
            __syncwarp();
            if (pwarp && elect_one()) {
                const uint32_t bar0 = bars + 8 * (BAR_FULL + rvp.slot), bar1 = bars + 8 * (BAR_FULL + rk.slot);
                if (PFD > 0 && j + 3 + PFD < NBLK) {
                    bulk_pf(gk + (size_t)(kvrow + (j + 3 + PFD) * 64) * 128, 16 * KB);
                    bulk_pf(gv + (size_t)(kvrow + (j + 3 + PFD) * 64) * 128, 16 * KB);
                }
                if (j > 0) mbar_wait(bars + 8 * (BAR_EMPTY + rvp.slot), rvp.par);
                if (j + 3 < NBLK) {
                    mbar_expect_tx(bar0, 16 * KB);
                    tma_3d(sa + SM_RING0 - rvp.slot * 16 * KB, &tmK, 0, kvrow + (j + 3) * 64, 0, bar0);
                } else {
                    load_wo_half(sa, &tmWo, 2 * (j + 3 - NBLK), kvh);
                }
                mbar_wait(bars + 8 * (BAR_EMPTY + rk.slot), rk.par);
                if (j + 3 < NBLK) {
                    mbar_expect_tx(bar1, 16 * KB);
                    tma_3d(sa + SM_RING0 - rk.slot * 16 * KB, &tmV, 0, kvrow + (j + 3) * 64, 0, bar1);
                } else {
                    load_wo_half(sa, &tmWo, 2 * (j + 3 - NBLK) + 1, kvh);
                }
                if (j == 26) bulk_pf(gwo + (size_t)(kvh * 256 + b * 32) * DM, 32 * DM * 2);
            }
            __syncwarp();
            rvp = rv;
            rk = rk1;
            wg_wait<0>();
#pragma unroll
            for (int i = 60; i < 64; i++) o[i] = split_copy(o[i]);
            if (elect_one()) mbar_arrive(bars + 8 * (BAR_EMPTY + rv.slot));
            __syncwarp();
        }
        {
            uint32_t pk[32];
            finish_l(l0, l1);
            pack_o_tile(pk, o, l0, l1);
            const uint32_t row = 128 - (kvh & 1) * 80 + (warp & 1) * 16 + ((lane >> 3) & 1) * 8 + (lane & 7);
            const uint32_t t = ((lane >> 4) ^ (lane & 7)) << 4;
            bar_sync(9, 384);
            store_o_tile(pk, sa + SM_Q + (warp >> 1) * 2 * 20480 + row * 128, t);
        }
        fence_async_smem();
    }
    oproj_phase(sa, wg, warp, b, kvh, &tmWo, out);
}

typedef CUresult (*EncodeTiledFn)(CUtensorMap*, CUtensorMapDataType, cuuint32_t, void*, const cuuint64_t*,
                                  const cuuint64_t*, const cuuint32_t*, const cuuint32_t*, CUtensorMapInterleave,
                                  CUtensorMapSwizzle, CUtensorMapL2promotion, CUtensorMapFloatOOBfill);

void encode(EncodeTiledFn fn, CUtensorMap* tm, const void* ptr, int rank, const cuuint64_t* dims,
            const cuuint64_t* strides, const cuuint32_t* box) {
    cuuint32_t es[3] = {1, 1, 1};
    fn(tm, CU_TENSOR_MAP_DATA_TYPE_BFLOAT16, rank, const_cast<void*>(ptr), dims, strides, box, es,
       CU_TENSOR_MAP_INTERLEAVE_NONE, CU_TENSOR_MAP_SWIZZLE_128B, CU_TENSOR_MAP_L2_PROMOTION_L2_256B,
       CU_TENSOR_MAP_FLOAT_OOB_FILL_NONE);
}

}

extern "C" void kernel_launch(void* const* d_in, const int* in_sizes, int n_in, void* d_out, int out_size) {
    const __nv_bfloat16* x = (const __nv_bfloat16*)d_in[0];
    const __nv_bfloat16* kc = (const __nv_bfloat16*)d_in[1];
    const __nv_bfloat16* vc = (const __nv_bfloat16*)d_in[2];
    const __nv_bfloat16* wq = (const __nv_bfloat16*)d_in[3];
    const __nv_bfloat16* wo = (const __nv_bfloat16*)d_in[4];

    void* fnp = nullptr;
    cudaDriverEntryPointQueryResult qres;
    cudaGetDriverEntryPoint("cuTensorMapEncodeTiled", &fnp, cudaEnableDefault, &qres);
    EncodeTiledFn fn = (EncodeTiledFn)fnp;

    CUtensorMap tmX, tmWq, tmK, tmV, tmWo;
    {
        cuuint64_t d[2] = {DM, (cuuint64_t)NB * SQ}, s[1] = {DM * 2};
        cuuint32_t bx[2] = {64, SQ};
        encode(fn, &tmX, x, 2, d, s, bx);
    }
    {
        cuuint64_t d[3] = {64, DM, 64}, s[2] = {4096 * 2, 128};
        cuuint32_t bx[3] = {64, 64, 4};
        encode(fn, &tmWq, wq, 3, d, s, bx);
    }
    {
        cuuint64_t d[3] = {64, (cuuint64_t)NB * HKV * SK, 2}, s[2] = {256, 128};
        cuuint32_t bx[3] = {64, 64, 2};
        encode(fn, &tmK, kc, 3, d, s, bx);
        encode(fn, &tmV, vc, 3, d, s, bx);
    }
    {
        cuuint64_t d[2] = {DM, 4096}, s[1] = {DM * 2};
        cuuint32_t bx[2] = {64, 128};
        encode(fn, &tmWo, wo, 2, d, s, bx);
    }
    cudaFuncSetAttribute(gqa_fused_kernel, cudaFuncAttributeMaxDynamicSharedMemorySize, SMEM_BYTES);
    gqa_fused_kernel<<<NB * HKV, 384, SMEM_BYTES>>>(tmX, tmWq, tmK, tmV, tmWo, kc, vc, wo, (__nv_bfloat16*)d_out);
}
```
